```python
import torch

def _softmax(x, axis=-1):
    return torch.softmax(x, dim=axis)

def _gelu(x):
    return torch.nn.functional.gelu(x, approximate='tanh')

def _silu(x):
    return torch.nn.functional.silu(x)

def _sigmoid(x):
    return torch.sigmoid(x)

def _layernorm(x, axis=-1, eps=1e-05):
    m = x.mean(dim=axis, keepdim=True)
    v = x.var(dim=axis, keepdim=True, unbiased=False)
    return (x - m) / torch.sqrt(v + eps)

def _scatter_add(tgt, idx, src, axis=0):
    return tgt.clone().index_add_(axis, idx, src)

def _segment_sum(src, seg, n):
    out = torch.zeros((n,) + src.shape[1:], dtype=src.dtype)
    return out.index_add_(0, seg, src)

def _pad(x, pw):
    flat = tuple((v for pair in reversed(pw) for v in pair))
    return torch.nn.functional.pad(x, flat)
kernel_name = 'adaLN_cond__gqa_block_cached__geglu_ffn__decode'

def setup_inputs():

    _w = lambda a: (lambda t: t.to(torch.bfloat16) if t.is_floating_point() else t)(torch.as_tensor(a))

    def _A_setup():
        B, Sq, D = (4, 1, 512)
        Hq, Hkv, Sk, Dh = (32, 8, 8192, 128)
        assert Hq % Hkv == 0, (Hq, Hkv)
        return {'x': _w((lambda *s: torch.randn(*s, dtype=torch.bfloat16) * 0.1)(B, Sq, D)), 'k_cache': _w((lambda *s: torch.randn(*s, dtype=torch.bfloat16) * 0.8)(B, Hkv, Sk, Dh)), 'v_cache': _w((lambda *s: torch.randn(*s, dtype=torch.bfloat16) * 1.6)(B, Hkv, Sk, Dh)), 'wq': _w((lambda *s: torch.randn(*s, dtype=torch.bfloat16) * 0.8)(D, Hq * Dh) * D ** (-0.5)), 'wo': _w((lambda *s: torch.randn(*s, dtype=torch.bfloat16) * 1.6)(Hq * Dh, D) * (Hq * Dh) ** (-0.5))}
    _A_in = _A_setup()

    def _B_setup():
        B, S, D, F = (4, 1, 512, 1792)
        return {'x': _w((lambda *s: torch.randn(*s, dtype=torch.bfloat16) * 0.1)(B, S, D)), 'w_gate': _w((lambda *s: torch.randn(*s, dtype=torch.bfloat16) * 0.1)(D, F)), 'w_up': _w((lambda *s: torch.randn(*s, dtype=torch.bfloat16) * 0.1)(D, F)), 'w_down': _w((lambda *s: torch.randn(*s, dtype=torch.bfloat16) * 0.1)(F, D))}
    _B_in = _B_setup()
    return {'A_x': _A_in['x'], 'A_k_cache': _A_in['k_cache'], 'A_v_cache': _A_in['v_cache'], 'A_wq': _A_in['wq'], 'A_wo': _A_in['wo'], 'B_x': _B_in['x'], 'B_w_gate': _B_in['w_gate'], 'B_w_up': _B_in['w_up'], 'B_w_down': _B_in['w_down'], 'c': _w((lambda *s: torch.randn(*s, dtype=torch.bfloat16) * 0.8)(4, 512) * 8.0), 'w_mod': _w((lambda *s: torch.randn(*s, dtype=torch.bfloat16) * 0.8)(512, 6 * 512) * 512 ** (-0.5) * 8.0)}

def reference(A_x, A_k_cache, A_v_cache, A_wq, A_wo, B_x, B_w_gate, B_w_up, B_w_down, c, w_mod):

    def _A_ref(x, k_cache, v_cache, wq, wo):
        B, Sq, D = x.shape
        Hq, Dh = (32, 128)
        Hkv = k_cache.shape[1]
        rep = Hq // Hkv
        q = (lambda x, *d: x.permute(*d))((x @ wq).reshape(B, Sq, Hq, Dh), 0, 2, 1, 3)
        k = (lambda x, n, axis: torch.repeat_interleave(x, n, dim=axis))(k_cache, rep, axis=1)
        v = (lambda x, n, axis: torch.repeat_interleave(x, n, dim=axis))(v_cache, rep, axis=1)
        scores = torch.einsum('bhqd,bhkd->bhqk', q, k) * Dh ** (-0.5)
        p = _softmax(scores, axis=-1)
        o = torch.einsum('bhqk,bhkd->bhqd', p, v)
        return (lambda x, *d: x.permute(*d))(o, 0, 2, 1, 3).reshape(B, Sq, Hq * Dh) @ wo

    def _B_ref(x, w_gate, w_up, w_down):
        return _gelu(x @ w_gate) * (x @ w_up) @ w_down
    x = A_x
    mod = (_silu(c) @ w_mod).reshape(c.shape[0], 6, 1, -1)
    sa, ca, ga, sb, cb, gb = (mod[:, 0].clone(), mod[:, 1].clone(), mod[:, 2].clone(), mod[:, 3].clone(), mod[:, 4].clone(), mod[:, 5].clone())
    h = _layernorm(x, axis=-1) * (1 + ca) + sa
    x = x + ga * _A_ref(h, A_k_cache, A_v_cache, A_wq, A_wo)
    h = _layernorm(x, axis=-1) * (1 + cb) + sb
    x = x + gb * _B_ref(h, B_w_gate, B_w_up, B_w_down)
    return x
```

```cpp
#include <cuda_runtime.h>
#include <cuda.h>
#include <cuda_bf16.h>
#include <stdint.h>

namespace {

typedef unsigned long long u64;
typedef __nv_bfloat16 bf16;

constexpr int NCTA = 128;
constexpr int NTHREADS = 288;
constexpr int NSLOT = 13;
constexpr int SLOT_BYTES = 16384;
constexpr int INFLIGHT = 4;
constexpr int TILES = 32;
constexpr int SEQ_WMODA = 0, SEQ_WQ = 1, SEQ_WMODB = 3, SEQ_KV = 4;
constexpr int SEQ_WO = SEQ_KV + 2 * TILES;
constexpr int NFFN = 112;
constexpr int DOWN0 = 64;

constexpr int SM_RING = 0;
constexpr int SM_H = SM_RING + NSLOT * SLOT_BYTES;
constexpr int SM_SB = SM_H + 4 * 520 * 2;
constexpr int SM_CB1 = SM_SB + 4 * 512 * 2;
constexpr int SM_RED = SM_CB1 + 4 * 512 * 2;
constexpr int SM_O = SM_RED + 8 * 128 * 4;
constexpr int SM_ML = SM_O + 4 * 136 * 2;
constexpr int SM_BAR = SM_ML + 8 * 4 * 8;
constexpr int SM_TOTAL = SM_BAR + 2 * NSLOT * 8;
static_assert(SM_TOTAL <= 232448, "smem");
static_assert(SM_H % 16 == 0 && SM_SB % 16 == 0 && SM_RED % 16 == 0 && SM_O % 16 == 0 && SM_ML % 16 == 0 && SM_BAR % 8 == 0, "align");

struct alignas(64) Params {
    CUtensorMap k, v, wmodA, wmodB, wq, wo, wg, wu, wd;
    const bf16* x;
    const bf16* c;
    bf16* out;
};

__device__ unsigned int g_epoch;
__device__ __align__(128) u64 g_modA[4 * 512];
__device__ __align__(128) u64 g_modB[4 * 1024];
__device__ __align__(128) u64 g_q[4 * 32 * 64];
__device__ __align__(128) u64 g_part[32 * 4 * 4 * 128];
__device__ __align__(128) u64 g_ml[32 * 4 * 4 * 2];
__device__ __align__(128) u64 g_p2[4 * 256 * 32 * 2];
__device__ __align__(128) u64 g_x1[4 * 256];
__device__ __align__(128) u64 g_act[NFFN * 32];

#define PROF(i) do {} while (0)

constexpr int SPIN_LIMIT = 1 << 22;

__device__ __forceinline__ uint32_t smem_u32(const void* p) { return (uint32_t)__cvta_generic_to_shared(p); }
__device__ __forceinline__ void mbar_init(uint32_t bar, uint32_t cnt) {
    asm volatile("mbarrier.init.shared.b64 [%0], %1;" ::"r"(bar), "r"(cnt) : "memory");
}
__device__ __forceinline__ void mbar_expect_tx(uint32_t bar, uint32_t bytes) {
    asm volatile("mbarrier.arrive.expect_tx.shared.b64 _, [%0], %1;" ::"r"(bar), "r"(bytes) : "memory");
}
__device__ __forceinline__ void mbar_arrive(uint32_t bar) {
    asm volatile("mbarrier.arrive.shared.b64 _, [%0];" ::"r"(bar) : "memory");
}
__device__ __forceinline__ bool mbar_try(uint32_t bar, uint32_t parity) {
    uint32_t ok;
    asm volatile("{\n.reg .pred p;\nmbarrier.try_wait.parity.shared.b64 p, [%1], %2;\nselp.u32 %0, 1, 0, p;\n}"
                 : "=r"(ok) : "r"(bar), "r"(parity) : "memory");
    return ok;
}
__device__ __forceinline__ void mbar_wait(uint32_t bar, uint32_t parity) {
    int n = 0;
    while (!mbar_try(bar, parity)) {
        if (++n > SPIN_LIMIT) __trap();
    }
}
__device__ __forceinline__ void tma_2d(uint32_t dst, const CUtensorMap* m, uint32_t bar, int c0, int c1, u64 pol) {
    asm volatile("cp.async.bulk.tensor.2d.shared::cluster.global.mbarrier::complete_tx::bytes.L2::cache_hint [%0], [%1, {%3, %4}], [%2], %5;"
                 ::"r"(dst), "l"(m), "r"(bar), "r"(c0), "r"(c1), "l"(pol) : "memory");
}
__device__ __forceinline__ void tma_3d(uint32_t dst, const CUtensorMap* m, uint32_t bar, int c0, int c1, int c2, u64 pol) {
    asm volatile("cp.async.bulk.tensor.3d.shared::cluster.global.mbarrier::complete_tx::bytes.L2::cache_hint [%0], [%1, {%3, %4, %5}], [%2], %6;"
                 ::"r"(dst), "l"(m), "r"(bar), "r"(c0), "r"(c1), "r"(c2), "l"(pol) : "memory");
}
__device__ __forceinline__ void ldsm4(uint32_t (&r)[4], uint32_t addr) {
    asm volatile("ldmatrix.sync.aligned.m8n8.x4.shared.b16 {%0,%1,%2,%3}, [%4];"
                 : "=r"(r[0]), "=r"(r[1]), "=r"(r[2]), "=r"(r[3]) : "r"(addr) : "memory");
}
__device__ __forceinline__ void ldsm4t(uint32_t (&r)[4], uint32_t addr) {
    asm volatile("ldmatrix.sync.aligned.m8n8.x4.trans.shared.b16 {%0,%1,%2,%3}, [%4];"
                 : "=r"(r[0]), "=r"(r[1]), "=r"(r[2]), "=r"(r[3]) : "r"(addr) : "memory");
}
__device__ __forceinline__ void mma16816(float (&c)[4], uint32_t a0, uint32_t a1, uint32_t a2, uint32_t a3, uint32_t b0, uint32_t b1) {
    asm volatile("mma.sync.aligned.m16n8k16.row.col.f32.bf16.bf16.f32 {%0,%1,%2,%3}, {%4,%5,%6,%7}, {%8,%9}, {%0,%1,%2,%3};"
                 : "+f"(c[0]), "+f"(c[1]), "+f"(c[2]), "+f"(c[3])
                 : "r"(a0), "r"(a1), "r"(a2), "r"(a3), "r"(b0), "r"(b1));
}
__device__ __forceinline__ uint32_t movmat(uint32_t a) {
    uint32_t d;
    asm volatile("movmatrix.sync.aligned.m8n8.trans.b16 %0, %1;" : "=r"(d) : "r"(a));
    return d;
}
__device__ __forceinline__ void cbar() { asm volatile("bar.sync 1, 256;" ::: "memory"); }

__device__ __forceinline__ float bfr(float x) { return __bfloat162float(__float2bfloat16_rn(x)); }
__device__ __forceinline__ uint32_t pack2(float lo, float hi) {
    __nv_bfloat162 v = __floats2bfloat162_rn(lo, hi);
    return *reinterpret_cast<uint32_t*>(&v);
}
__device__ __forceinline__ float bflo(uint32_t w) { return __uint_as_float(w << 16); }
__device__ __forceinline__ float bfhi(uint32_t w) { return __uint_as_float(w & 0xffff0000u); }
__device__ __forceinline__ float ex2(float x) {
    float y;
    asm("ex2.approx.ftz.f32 %0, %1;" : "=f"(y) : "f"(x));
    return y;
}

__device__ __forceinline__ void ll_st1(u64* p, uint32_t d, uint32_t ep) {
    u64 v = ((u64)ep << 32) | d;
    asm volatile("st.relaxed.gpu.global.u64 [%0], %1;" ::"l"(p), "l"(v) : "memory");
}
__device__ __forceinline__ void ll_st2(u64* p, uint32_t d0, uint32_t d1, uint32_t ep) {
    u64 v0 = ((u64)ep << 32) | d0, v1 = ((u64)ep << 32) | d1;
    asm volatile("st.relaxed.gpu.global.v2.u64 [%0], {%1, %2};" ::"l"(p), "l"(v0), "l"(v1) : "memory");
}
__device__ __forceinline__ bool ll_ld1(const u64* p, uint32_t& d, uint32_t ep) {
    u64 v;
    asm volatile("ld.relaxed.gpu.global.u64 %0, [%1];" : "=l"(v) : "l"(p) : "memory");
    d = (uint32_t)v;
    return (uint32_t)(v >> 32) == ep;
}
__device__ __forceinline__ bool ll_ld2(const u64* p, uint32_t& d0, uint32_t& d1, uint32_t ep) {
    u64 v0, v1;
    asm volatile("ld.relaxed.gpu.global.v2.u64 {%0, %1}, [%2];" : "=l"(v0), "=l"(v1) : "l"(p) : "memory");
    d0 = (uint32_t)v0;
    d1 = (uint32_t)v1;
    return ((uint32_t)(v0 >> 32) == ep) & ((uint32_t)(v1 >> 32) == ep);
}
#define LL_SPIN(cond_expr)                         \
    do {                                           \
        int _n = 0;                                \
        while (!(cond_expr)) {                     \
            if (++_n > SPIN_LIMIT) __trap();       \
        }                                          \
    } while (0)

__device__ __forceinline__ float silu_bf(float x) { return x / (1.0f + __expf(-x)); }

__device__ __forceinline__ float warp_sum(float v) {
#pragma unroll
    for (int o = 16; o > 0; o >>= 1) v += __shfl_xor_sync(0xffffffffu, v, o);
    return v;
}

__global__ void __launch_bounds__(NTHREADS, 1) fused_kernel(const __grid_constant__ Params p) {
    extern __shared__ __align__(1024) unsigned char smem[];
    const uint32_t sbase = smem_u32(smem);
    const uint32_t ring = sbase + SM_RING;
    const uint32_t bar_full = sbase + SM_BAR, bar_empty = bar_full + NSLOT * 8;
    const int tid = threadIdx.x, warp = tid >> 5, lane = tid & 31;
    const int j = blockIdx.x;
    const int kvh = j >> 4, ab = (j >> 2) & 3, split = j & 3;
    const bool has_ffn = j < NFFN, has_down = j >= DOWN0;

    PROF(0);
    if (tid == 256) {
        if (sbase & 1023) __trap();
        for (int i = 0; i < NSLOT; i++) {
            mbar_init(bar_full + i * 8, 1);
            mbar_init(bar_empty + i * 8, 4);
        }
        asm volatile("fence.mbarrier_init.release.cluster;" ::: "memory");
        asm volatile("fence.proxy.async.shared::cta;" ::: "memory");
    }
    __syncthreads();

    if (warp == 8) {
        if (lane == 0) {
            u64 pol;
            asm volatile("createpolicy.fractional.L2::evict_first.b64 %0, 1.0;" : "=l"(pol));
            u64 poln;
            asm volatile("createpolicy.fractional.L2::evict_normal.b64 %0, 1.0;" : "=l"(poln));
            const int row0 = (ab * 8 + kvh) * 8192 + split * 2048;
            const int nseq = SEQ_WO + 2 + (has_ffn ? 2 : 0) + (has_down ? 2 : 0);
            int s = 0, ph = 1, s2 = 0, ph2 = 0;
            for (int n = 0; n < nseq; n++) {
                mbar_wait(bar_empty + s * 8, ph);
                if (n >= INFLIGHT) {
                    mbar_wait(bar_full + s2 * 8, ph2);
                    if (++s2 == NSLOT) { s2 = 0; ph2 ^= 1; }
                }
                const uint32_t fb = bar_full + s * 8, dst = ring + s * SLOT_BYTES;
                if (n >= SEQ_KV && n < SEQ_WO) {
                    const int i = n - SEQ_KV;
                    mbar_expect_tx(fb, 16384);
                    tma_3d(dst, (i & 1) ? &p.v : &p.k, fb, 0, row0 + (i >> 1) * 64, 0, pol);
                } else if (n == SEQ_WMODA) {
                    mbar_expect_tx(fb, 8192);
                    tma_2d(dst, &p.wmodA, fb, 8 * j, 0, poln);
                    tma_2d(dst + 4096, &p.wmodA, fb, 8 * j, 256, poln);
                } else if (n < SEQ_WMODB) {
                    mbar_expect_tx(fb, 16384);
                    tma_2d(dst, &p.wq, fb, 32 * j, (n - SEQ_WQ) * 256, poln);
                } else if (n == SEQ_WMODB) {
                    mbar_expect_tx(fb, 16384);
                    tma_2d(dst, &p.wmodB, fb, 1024 + 16 * j, 0, poln);
                    tma_2d(dst + 8192, &p.wmodB, fb, 1024 + 16 * j, 256, poln);
                } else if (n < SEQ_WO + 2) {
                    mbar_expect_tx(fb, 16384);
                    tma_2d(dst, &p.wo, fb, (j & 3) * 128 + (n - SEQ_WO) * 64, (j >> 2) * 128, pol);
                } else {
                    int r = n - (SEQ_WO + 2);
                    if (has_ffn && r < 2) {
                        const CUtensorMap* m = r ? &p.wu : &p.wg;
                        mbar_expect_tx(fb, 16384);
                        tma_2d(dst, m, fb, 16 * j, 0, poln);
                        tma_2d(dst + 8192, m, fb, 16 * j, 256, poln);
                    } else {
                        if (has_ffn) r -= 2;
                        const int nb = r ? 3 : 4;
                        mbar_expect_tx(fb, nb * 4096);
                        for (int q = 0; q < nb; q++)
                            tma_2d(dst + q * 4096, &p.wd, fb, 8 * (j - DOWN0), (r * 4 + q) * 256, poln);
                    }
                }
                if (++s == NSLOT) { s = 0; ph ^= 1; }
            }
        }
        return;
    }

    const int g = lane >> 2, t = lane & 3;
    unsigned int ep;
    asm volatile("ld.relaxed.gpu.global.u32 %0, [%1];" : "=r"(ep) : "l"(&g_epoch) : "memory");
    ep += 1;

    float* red = reinterpret_cast<float*>(smem + SM_RED);
    bf16* h_s = reinterpret_cast<bf16*>(smem + SM_H);
    const uint32_t h_su = sbase + SM_H;

    uint32_t sc[8];
#pragma unroll
    for (int i = 0; i < 8; i++) sc[i] = 0;
    if (g < 4) {
        const uint32_t* cw = reinterpret_cast<const uint32_t*>(p.c + g * 512 + warp * 64 + 2 * t);
#pragma unroll
        for (int i = 0; i < 8; i++) {
            uint32_t w = __ldg(cw + i * 4);
            sc[i] = pack2(silu_bf(bflo(w)), silu_bf(bfhi(w)));
        }
    }
    float nx[8];
    {
        const int b = tid >> 6;
        const uint4* xr = reinterpret_cast<const uint4*>(p.x + b * 512);
        uint4 u0 = __ldg(xr + lane * 2), u1 = __ldg(xr + lane * 2 + 1);
        uint4 own = __ldg(xr + (tid & 63));
        uint32_t w[8] = {u0.x, u0.y, u0.z, u0.w, u1.x, u1.y, u1.z, u1.w};
        float sum = 0.f;
#pragma unroll
        for (int i = 0; i < 8; i++) sum += bflo(w[i]) + bfhi(w[i]);
        const float mean = warp_sum(sum) * (1.0f / 512.0f);
        float sq = 0.f;
#pragma unroll
        for (int i = 0; i < 8; i++) {
            float a = bflo(w[i]) - mean, bb = bfhi(w[i]) - mean;
            sq += a * a + bb * bb;
        }
        const float var = warp_sum(sq) * (1.0f / 512.0f);
        const float mb = bfr(mean), den = bfr(sqrtf(bfr(bfr(var) + 1e-5f)));
        uint32_t ow[4] = {own.x, own.y, own.z, own.w};
#pragma unroll
        for (int i = 0; i < 4; i++) {
            nx[2 * i] = bfr(bfr(bflo(ow[i]) - mb) / den);
            nx[2 * i + 1] = bfr(bfr(bfhi(ow[i]) - mb) / den);
        }
    }

    {
        const uint32_t slot = ring + (SEQ_WMODA % NSLOT) * SLOT_BYTES;
        mbar_wait(bar_full + (SEQ_WMODA % NSLOT) * 8, 0);
        float c[4] = {0.f, 0.f, 0.f, 0.f};
#pragma unroll
        for (int i = 0; i < 2; i++) {
            uint32_t r[4];
            ldsm4t(r, slot + (warp * 64 + i * 32 + lane) * 16);
            mma16816(c, sc[4 * i], 0, sc[4 * i + 1], 0, r[0], r[1]);
            mma16816(c, sc[4 * i + 2], 0, sc[4 * i + 3], 0, r[2], r[3]);
        }
        if (g < 4) *reinterpret_cast<float2*>(red + warp * 128 + g * 8 + 2 * t) = make_float2(c[0], c[1]);
        cbar();
        if (tid < 16) {
            float s0 = 0.f, s1 = 0.f;
#pragma unroll
            for (int w = 0; w < 8; w++) {
                float2 v = *reinterpret_cast<float2*>(red + w * 128 + tid * 2);
                s0 += v.x; s1 += v.y;
            }
            ll_st1(&g_modA[(tid >> 2) * 512 + 4 * j + (tid & 3)], pack2(s0, s1), ep);
        }
    }
    PROF(1);
    {
        const int b = tid >> 6, i = tid & 63;
        uint32_t sa[4], ca[4];
        const u64* ps = &g_modA[b * 512 + 4 * i];
        LL_SPIN(ll_ld2(ps, sa[0], sa[1], ep) & ll_ld2(ps + 2, sa[2], sa[3], ep) &
                ll_ld2(ps + 256, ca[0], ca[1], ep) & ll_ld2(ps + 258, ca[2], ca[3], ep));
        uint32_t hw[4];
#pragma unroll
        for (int q = 0; q < 4; q++) {
            float h0 = bfr(nx[2 * q] * bfr(1.0f + bflo(ca[q]))) + bflo(sa[q]);
            float h1 = bfr(nx[2 * q + 1] * bfr(1.0f + bfhi(ca[q]))) + bfhi(sa[q]);
            hw[q] = pack2(h0, h1);
        }
        *reinterpret_cast<uint4*>(h_s + b * 520 + 8 * i) = make_uint4(hw[0], hw[1], hw[2], hw[3]);
        cbar();
    }
    PROF(2);
    {
        const int sq = SEQ_WQ + (warp >> 2);
        const uint32_t slot = ring + (sq % NSLOT) * SLOT_BYTES;
        mbar_wait(bar_full + (sq % NSLOT) * 8, 0);
        float c0[4] = {0.f, 0.f, 0.f, 0.f}, c1[4] = {0.f, 0.f, 0.f, 0.f};
#pragma unroll
        for (int ks = 0; ks < 4; ks++) {
            uint32_t b0 = 0, b1 = 0;
            if (g < 4) {
                const uint32_t* hp = reinterpret_cast<const uint32_t*>(h_s + g * 520 + warp * 64 + ks * 16 + 2 * t);
                b0 = hp[0]; b1 = hp[4];
            }
            const int row = (warp & 3) * 64 + ks * 16 + (lane & 7) + (lane >> 4) * 8;
            const int sw = (row >> 1) & 3;
            const int ch = (lane >> 3) & 1;
            uint32_t a[4];
            ldsm4t(a, slot + row * 64 + ((ch ^ sw) << 4));
            mma16816(c0, a[0], a[1], a[2], a[3], b0, b1);
            ldsm4t(a, slot + row * 64 + (((2 + ch) ^ sw) << 4));
            mma16816(c1, a[0], a[1], a[2], a[3], b0, b1);
        }
        if (t < 2) {
            float* rw = red + warp * 128 + 2 * t;
            *reinterpret_cast<float2*>(rw + g * 4) = make_float2(c0[0], c0[1]);
            *reinterpret_cast<float2*>(rw + (g + 8) * 4) = make_float2(c0[2], c0[3]);
            *reinterpret_cast<float2*>(rw + (g + 16) * 4) = make_float2(c1[0], c1[1]);
            *reinterpret_cast<float2*>(rw + (g + 24) * 4) = make_float2(c1[2], c1[3]);
        }
        cbar();
        if (tid < 64) {
            const int b = tid >> 4, tt = (tid >> 2) & 3, ksl = (tid >> 1) & 1, hi = tid & 1;
            const int col = 16 * ksl + 8 * hi + 2 * tt;
            float s0 = 0.f, s1 = 0.f;
#pragma unroll
            for (int w = 0; w < 8; w++) {
                s0 += red[w * 128 + col * 4 + b];
                s1 += red[w * 128 + (col + 1) * 4 + b];
            }
            const int head = j >> 2, ks = 2 * (j & 3) + ksl;
            ll_st1(&g_q[(((b * 32 + head) * 4 + tt) * 8 + ks) * 2 + hi], pack2(s0, s1), ep);
        }
        if (warp >= 4 && lane == 0) {
            mbar_arrive(bar_empty + (SEQ_WMODA % NSLOT) * 8);
            mbar_arrive(bar_empty + (SEQ_WQ % NSLOT) * 8);
            mbar_arrive(bar_empty + ((SEQ_WQ + 1) % NSLOT) * 8);
        }
        cbar();
    }
    PROF(3);
    {
        const uint32_t slot = ring + (SEQ_WMODB % NSLOT) * SLOT_BYTES;
        mbar_wait(bar_full + (SEQ_WMODB % NSLOT) * 8, 0);
        float c0[4] = {0.f, 0.f, 0.f, 0.f}, c1[4] = {0.f, 0.f, 0.f, 0.f};
#pragma unroll
        for (int ks = 0; ks < 4; ks++) {
            const int row = warp * 64 + ks * 16 + (lane & 15);
            const int ch = (lane >> 4) ^ ((row >> 2) & 1);
            uint32_t r[4];
            ldsm4t(r, slot + row * 32 + (ch << 4));
            mma16816(c0, sc[2 * ks], 0, sc[2 * ks + 1], 0, r[0], r[1]);
            mma16816(c1, sc[2 * ks], 0, sc[2 * ks + 1], 0, r[2], r[3]);
        }
        if (g < 4) {
            *reinterpret_cast<float2*>(red + warp * 128 + g * 16 + 2 * t) = make_float2(c0[0], c0[1]);
            *reinterpret_cast<float2*>(red + warp * 128 + g * 16 + 8 + 2 * t) = make_float2(c1[0], c1[1]);
        }
        cbar();
        if (tid < 32) {
            float s0 = 0.f, s1 = 0.f;
#pragma unroll
            for (int w = 0; w < 8; w++) {
                float2 v = *reinterpret_cast<float2*>(red + w * 128 + tid * 2);
                s0 += v.x; s1 += v.y;
            }
            ll_st1(&g_modB[(tid >> 3) * 1024 + 8 * j + (tid & 7)], pack2(s0, s1), ep);
        }
        if (warp >= 4 && lane == 0) mbar_arrive(bar_empty + (SEQ_WMODB % NSLOT) * 8);
    }
    uint32_t qf[16];
#pragma unroll
    for (int i = 0; i < 16; i++) qf[i] = 0;
    if (g < 4) {
        const u64* qp = &g_q[((ab * 32 + kvh * 4 + g) * 4 + t) * 16];
        int n = 0;
        while (true) {
            bool ok = true;
#pragma unroll
            for (int ks = 0; ks < 8; ks++) ok &= ll_ld2(qp + 2 * ks, qf[2 * ks], qf[2 * ks + 1], ep);
            if (ok) break;
            if (++n > SPIN_LIMIT) __trap();
        }
    }
    __syncwarp();
    PROF(4);

    const int gw = j * 8 + warp;
    const int rb = gw >> 8, rcp = gw & 255;
    uint32_t ga2 = 0, gb2 = 0;

    const int grp = warp >> 2, wq4 = warp & 3;
    float o[8][4];
#pragma unroll
    for (int i = 0; i < 8; i++) { o[i][0] = o[i][1] = o[i][2] = o[i][3] = 0.f; }
    float m0 = -INFINITY, m1 = -INFINITY, l0 = 0.f, l1 = 0.f;
    const float LOG2E = 1.4426950408889634f;
    const float SCALE = 0.08838834764831845f;
    const int krow = wq4 * 16 + (lane & 15);
    const uint32_t koff = krow * 128, kx = krow & 7, kc = lane >> 4;
    const int vrow = wq4 * 16 + (lane & 7) + (lane >> 4) * 8;
    const uint32_t voff = vrow * 128, vx = vrow & 7, vc = (lane >> 3) & 1;

    uint32_t kslot_last = 0;
    for (int it = 0; it < TILES / 2; it++) {
        const int nk = SEQ_KV + 2 * (2 * it + grp), nv = nk + 1;
        const int sk = nk % NSLOT, sv = nv % NSLOT;
        const uint32_t kbase = ring + sk * SLOT_BYTES, vbase = ring + sv * SLOT_BYTES;
        kslot_last = kbase;
        if (it == 8) {
            const int b = tid >> 6, i = tid & 63;
            uint32_t sb[4], cb[4];
            const u64* ps = &g_modB[b * 1024 + 256 + 4 * i];
            LL_SPIN(ll_ld2(ps, sb[0], sb[1], ep) & ll_ld2(ps + 2, sb[2], sb[3], ep) &
                    ll_ld2(ps + 256, cb[0], cb[1], ep) & ll_ld2(ps + 258, cb[2], cb[3], ep) &
                    ll_ld1(&g_modB[rb * 1024 + rcp], ga2, ep) &
                    ll_ld1(&g_modB[((tid >> 2) & 3) * 1024 + 768 + 4 * (j & 63) + (tid & 3)], gb2, ep));
#pragma unroll
            for (int q = 0; q < 4; q++) cb[q] = pack2(1.0f + bflo(cb[q]), 1.0f + bfhi(cb[q]));
            *reinterpret_cast<uint4*>(smem + SM_SB + (b * 512 + 8 * i) * 2) = make_uint4(sb[0], sb[1], sb[2], sb[3]);
            *reinterpret_cast<uint4*>(smem + SM_CB1 + (b * 512 + 8 * i) * 2) = make_uint4(cb[0], cb[1], cb[2], cb[3]);
            __syncwarp();
        }
        mbar_wait(bar_full + sk * 8, (nk / NSLOT) & 1);
        float sa[4] = {0.f, 0.f, 0.f, 0.f}, sb_[4] = {0.f, 0.f, 0.f, 0.f};
#pragma unroll
        for (int ks = 0; ks < 8; ks++) {
            const uint32_t ch = 2 * ks + kc;
            uint32_t a[4];
            ldsm4(a, kbase + (ch >> 3) * 8192 + koff + (((ch & 7) ^ kx) << 4));
            if (ks & 1) mma16816(sb_, a[0], a[1], a[2], a[3], qf[2 * ks], qf[2 * ks + 1]);
            else        mma16816(sa, a[0], a[1], a[2], a[3], qf[2 * ks], qf[2 * ks + 1]);
        }
        __syncwarp();
        if (lane == 0 && it != TILES / 2 - 1) mbar_arrive(bar_empty + sk * 8);
        float s[4];
#pragma unroll
        for (int i = 0; i < 4; i++) s[i] = bfr(bfr(sa[i] + sb_[i]) * SCALE);
        float x0 = fmaxf(s[0], s[2]), x1 = fmaxf(s[1], s[3]);
#pragma unroll
        for (int off = 4; off < 32; off <<= 1) {
            x0 = fmaxf(x0, __shfl_xor_sync(0xffffffffu, x0, off));
            x1 = fmaxf(x1, __shfl_xor_sync(0xffffffffu, x1, off));
        }
        const float n0 = fmaxf(m0, x0), n1 = fmaxf(m1, x1);
        const float al0 = ex2((m0 - n0) * LOG2E), al1 = ex2((m1 - n1) * LOG2E);
        m0 = n0; m1 = n1;
        const float p0 = ex2((s[0] - n0) * LOG2E), p1 = ex2((s[1] - n1) * LOG2E);
        const float p2 = ex2((s[2] - n0) * LOG2E), p3 = ex2((s[3] - n1) * LOG2E);
        l0 = l0 * al0 + (p0 + p2);
        l1 = l1 * al1 + (p1 + p3);
        const uint32_t pb0 = movmat(pack2(p0, p1)), pb1 = movmat(pack2(p2, p3));
#pragma unroll
        for (int mt = 0; mt < 8; mt++) {
            o[mt][0] *= al0; o[mt][1] *= al1; o[mt][2] *= al0; o[mt][3] *= al1;
        }
        mbar_wait(bar_full + sv * 8, (nv / NSLOT) & 1);
#pragma unroll
        for (int mt = 0; mt < 8; mt++) {
            const uint32_t ch = 2 * mt + vc;
            uint32_t a[4];
            ldsm4t(a, vbase + (ch >> 3) * 8192 + voff + (((ch & 7) ^ vx) << 4));
            mma16816(o[mt], a[0], a[1], a[2], a[3], pb0, pb1);
        }
        __syncwarp();
        if (lane == 0) mbar_arrive(bar_empty + sv * 8);
    }
    PROF(5);

    {
#pragma unroll
        for (int off = 4; off < 32; off <<= 1) {
            l0 += __shfl_xor_sync(0xffffffffu, l0, off);
            l1 += __shfl_xor_sync(0xffffffffu, l1, off);
        }
        float* so = reinterpret_cast<float*>(smem + (kslot_last - sbase) + wq4 * 2048);
        float2* ml = reinterpret_cast<float2*>(smem + SM_ML);
        if (t < 2) {
            const int x = t << 4;
#pragma unroll
            for (int mt = 0; mt < 8; mt++) {
                const int d = 16 * mt + g;
                so[(2 * t) * 128 + (d ^ x)] = o[mt][0];
                so[(2 * t + 1) * 128 + (d ^ x)] = o[mt][1];
                so[(2 * t) * 128 + ((d + 8) ^ x)] = o[mt][2];
                so[(2 * t + 1) * 128 + ((d + 8) ^ x)] = o[mt][3];
            }
            if (g == 0) {
                ml[warp * 4 + 2 * t] = make_float2(m0, l0);
                ml[warp * 4 + 2 * t + 1] = make_float2(m1, l1);
            }
        }
        cbar();
        const int hd = tid >> 6, dp = tid & 63;
        float2 v[8];
        float M = -INFINITY;
#pragma unroll
        for (int w = 0; w < 8; w++) { v[w] = ml[w * 4 + hd]; M = fmaxf(M, v[w].x); }
        float L = 0.f, a0 = 0.f, a1 = 0.f;
#pragma unroll
        for (int w = 0; w < 8; w++) {
            const float sc_w = ex2((v[w].x - M) * LOG2E);
            L += v[w].y * sc_w;
            const int nkl = SEQ_KV + 2 * (TILES - 2 + (w >> 2));
            const float* sw = reinterpret_cast<const float*>(smem + SM_RING + (nkl % NSLOT) * SLOT_BYTES + (w & 3) * 2048);
            const float2 ov = *reinterpret_cast<const float2*>(sw + hd * 128 + ((2 * dp) ^ ((hd >> 1) << 4)));
            a0 += ov.x * sc_w; a1 += ov.y * sc_w;
        }
        const int prow = ((kvh * 4 + hd) * 4 + ab) * 4 + split;
        ll_st2(&g_part[prow * 128 + 2 * dp], __float_as_uint(a0), __float_as_uint(a1), ep);
        if (dp == 0) ll_st2(&g_ml[prow * 2], __float_as_uint(M), __float_as_uint(L), ep);
    }
    PROF(6);

    {
        const int head = j >> 2, nq = j & 3;
        const int b = tid >> 6, dp = tid & 63;
        uint32_t ov[8], mlv[8];
        const u64* pp = &g_part[((head * 4 + b) * 4) * 128 + 2 * dp];
        const u64* pm = &g_ml[((head * 4 + b) * 4) * 2];
        int n = 0;
        while (true) {
            bool ok = true;
#pragma unroll
            for (int s = 0; s < 4; s++) {
                ok &= ll_ld2(pp + s * 128, ov[2 * s], ov[2 * s + 1], ep);
                ok &= ll_ld2(pm + s * 2, mlv[2 * s], mlv[2 * s + 1], ep);
            }
            if (ok) break;
            if (++n > SPIN_LIMIT) __trap();
        }
        float M = -INFINITY;
#pragma unroll
        for (int s = 0; s < 4; s++) M = fmaxf(M, __uint_as_float(mlv[2 * s]));
        float L = 0.f, a0 = 0.f, a1 = 0.f;
#pragma unroll
        for (int s = 0; s < 4; s++) {
            const float w = ex2((__uint_as_float(mlv[2 * s]) - M) * LOG2E);
            L += __uint_as_float(mlv[2 * s + 1]) * w;
            a0 += __uint_as_float(ov[2 * s]) * w;
            a1 += __uint_as_float(ov[2 * s + 1]) * w;
        }
        bf16* o_s = reinterpret_cast<bf16*>(smem + SM_O);
        *reinterpret_cast<uint32_t*>(o_s + b * 136 + 2 * dp) = pack2(a0 / L, a1 / L);
        cbar();
        PROF(7);
        const int sq = SEQ_WO + (warp >> 2);
        const uint32_t slot = ring + (sq % NSLOT) * SLOT_BYTES;
        mbar_wait(bar_full + (sq % NSLOT) * 8, (sq / NSLOT) & 1);
        float c0[4] = {0.f, 0.f, 0.f, 0.f}, c1[4] = {0.f, 0.f, 0.f, 0.f};
        const int ch = 2 * (warp & 3) + ((lane >> 3) & 1);
#pragma unroll
        for (int ks = 0; ks < 8; ks++) {
            uint32_t b0 = 0, b1 = 0;
            if (g < 4) {
                const uint32_t* op = reinterpret_cast<const uint32_t*>(o_s + g * 136 + ks * 16 + 2 * t);
                b0 = op[0]; b1 = op[4];
            }
            const int row = ks * 16 + (lane & 7) + (lane >> 4) * 8;
            uint32_t a[4];
            ldsm4t(a, slot + row * 128 + ((ch ^ (row & 7)) << 4));
            if (ks & 1) mma16816(c1, a[0], a[1], a[2], a[3], b0, b1);
            else        mma16816(c0, a[0], a[1], a[2], a[3], b0, b1);
        }
        if (t < 2) {
            const int col = nq * 128 + warp * 16 + g;
#pragma unroll
            for (int i = 0; i < 4; i++) {
                const int cc = col + (i >> 1) * 8, bb = 2 * t + (i & 1);
                ll_st1(&g_p2[((bb * 256 + (cc >> 1)) * 32 + head) * 2 + (cc & 1)], __float_as_uint(c0[i] + c1[i]), ep);
            }
        }
    }
    PROF(8);
    {
        const uint32_t xw = __ldg(reinterpret_cast<const uint32_t*>(p.x + rb * 512 + 2 * rcp));
        uint32_t d0, d1;
        const u64* pp = &g_p2[((rb * 256 + rcp) * 32 + lane) * 2];
        LL_SPIN(ll_ld2(pp, d0, d1, ep));
        const float s0 = warp_sum(__uint_as_float(d0)), s1 = warp_sum(__uint_as_float(d1));
        if (lane == 0) {
            const float y0 = bflo(xw) + bfr(bflo(ga2) * bfr(s0));
            const float y1 = bfhi(xw) + bfr(bfhi(ga2) * bfr(s1));
            ll_st1(&g_x1[rb * 256 + rcp], pack2(y0, y1), ep);
        }
    }
    PROF(9);
    int seq_next = SEQ_WO + 2;
    if (has_ffn) {
        if (warp < 4) {
            const int b = warp;
            uint32_t w[8];
            const u64* px = &g_x1[b * 256 + 2 * lane];
            LL_SPIN(ll_ld2(px, w[0], w[1], ep) & ll_ld2(px + 64, w[2], w[3], ep) &
                    ll_ld2(px + 128, w[4], w[5], ep) & ll_ld2(px + 192, w[6], w[7], ep));
            float sum = 0.f;
#pragma unroll
            for (int i = 0; i < 8; i++) sum += bflo(w[i]) + bfhi(w[i]);
            const float mean = warp_sum(sum) * (1.0f / 512.0f);
            float sq = 0.f;
#pragma unroll
            for (int i = 0; i < 8; i++) {
                float a = bflo(w[i]) - mean, bb = bfhi(w[i]) - mean;
                sq += a * a + bb * bb;
            }
            const float var = warp_sum(sq) * (1.0f / 512.0f);
            const float mb = bfr(mean), den = bfr(sqrtf(bfr(bfr(var) + 1e-5f)));
#pragma unroll
            for (int i = 0; i < 4; i++) {
                const int col = 128 * i + 4 * lane;
                const uint2 sbv = *reinterpret_cast<const uint2*>(smem + SM_SB + (b * 512 + col) * 2);
                const uint2 cbv = *reinterpret_cast<const uint2*>(smem + SM_CB1 + (b * 512 + col) * 2);
                const float n0 = bfr(bfr(bflo(w[2 * i]) - mb) / den), n1 = bfr(bfr(bfhi(w[2 * i]) - mb) / den);
                const float n2 = bfr(bfr(bflo(w[2 * i + 1]) - mb) / den), n3 = bfr(bfr(bfhi(w[2 * i + 1]) - mb) / den);
                uint2 hv;
                hv.x = pack2(bfr(n0 * bflo(cbv.x)) + bflo(sbv.x), bfr(n1 * bfhi(cbv.x)) + bfhi(sbv.x));
                hv.y = pack2(bfr(n2 * bflo(cbv.y)) + bflo(sbv.y), bfr(n3 * bfhi(cbv.y)) + bfhi(sbv.y));
                *reinterpret_cast<uint2*>(h_s + b * 520 + col) = hv;
            }
            if (j == 0 && tid == 0) {
                asm volatile("st.relaxed.gpu.global.u32 [%0], %1;" ::"l"(&g_epoch), "r"(ep) : "memory");
            }
        }
        cbar();
        PROF(10);
        const int sg = seq_next, su = seq_next + 1;
        seq_next += 2;
        const uint32_t slot_g = ring + (sg % NSLOT) * SLOT_BYTES, slot_u = ring + (su % NSLOT) * SLOT_BYTES;
        mbar_wait(bar_full + (sg % NSLOT) * 8, (sg / NSLOT) & 1);
        mbar_wait(bar_full + (su % NSLOT) * 8, (su / NSLOT) & 1);
        float cg[4] = {0.f, 0.f, 0.f, 0.f}, cu[4] = {0.f, 0.f, 0.f, 0.f};
#pragma unroll
        for (int ks = 0; ks < 4; ks++) {
            uint32_t b0 = 0, b1 = 0;
            if (g < 4) {
                const uint32_t* hp = reinterpret_cast<const uint32_t*>(h_s + g * 520 + warp * 64 + ks * 16 + 2 * t);
                b0 = hp[0]; b1 = hp[4];
            }
            const int row = warp * 64 + ks * 16 + (lane & 7) + (lane >> 4) * 8;
            const int ch = ((lane >> 3) & 1) ^ ((row >> 2) & 1);
            uint32_t a[4];
            ldsm4t(a, slot_g + row * 32 + (ch << 4));
            mma16816(cg, a[0], a[1], a[2], a[3], b0, b1);
            ldsm4t(a, slot_u + row * 32 + (ch << 4));
            mma16816(cu, a[0], a[1], a[2], a[3], b0, b1);
        }
        if (t < 2) {
            float* rw = red + warp * 128 + 2 * t;
            *reinterpret_cast<float2*>(rw + g * 4) = make_float2(cg[0], cg[1]);
            *reinterpret_cast<float2*>(rw + (g + 8) * 4) = make_float2(cg[2], cg[3]);
            *reinterpret_cast<float2*>(rw + 64 + g * 4) = make_float2(cu[0], cu[1]);
            *reinterpret_cast<float2*>(rw + 64 + (g + 8) * 4) = make_float2(cu[2], cu[3]);
        }
        cbar();
        if (tid < 64) {
            const int b = tid >> 4, tt = (tid >> 2) & 3, hi = (tid >> 1) & 1, e = tid & 1;
            const int f = 8 * hi + 2 * tt + e;
            float sgv = 0.f, suv = 0.f;
#pragma unroll
            for (int w = 0; w < 8; w++) {
                sgv += red[w * 128 + f * 4 + b];
                suv += red[w * 128 + 64 + f * 4 + b];
            }
            const float gv = bfr(sgv), uv = bfr(suv);
            const float inner = 0.7978845608028654f * (gv + 0.044715f * gv * gv * gv);
            const float ge = bfr(0.5f * gv * (1.0f + tanhf(inner)));
            const float av = ge * uv;
            const float other = __shfl_xor_sync(0xffffffffu, av, 1);
            if (e == 0) ll_st1(&g_act[j * 32 + (b * 4 + tt) * 2 + hi], pack2(av, other), ep);
        }
        PROF(11);
    }
    if (has_down) {
        uint32_t af[28];
#pragma unroll
        for (int i = 0; i < 28; i++) af[i] = 0;
        uint32_t x1w = 0;
        if (tid < 16) LL_SPIN(ll_ld1(&g_x1[(tid >> 2) * 256 + 4 * (j - DOWN0) + (tid & 3)], x1w, ep));
        if (g < 4) {
            const u64* pa = &g_act[(warp * 14) * 32 + (g * 4 + t) * 2];
            int n = 0;
            while (true) {
                bool ok = true;
#pragma unroll
                for (int ks = 0; ks < 14; ks++) ok &= ll_ld2(pa + ks * 32, af[2 * ks], af[2 * ks + 1], ep);
                if (ok) break;
                if (++n > SPIN_LIMIT) __trap();
            }
        }
        __syncwarp();
        PROF(12);
        const int sd = seq_next;
        mbar_wait(bar_full + (sd % NSLOT) * 8, (sd / NSLOT) & 1);
        mbar_wait(bar_full + ((sd + 1) % NSLOT) * 8, ((sd + 1) / NSLOT) & 1);
        float c0[4] = {0.f, 0.f, 0.f, 0.f}, c1[4] = {0.f, 0.f, 0.f, 0.f};
#pragma unroll
        for (int i = 0; i < 7; i++) {
            const int row = warp * 224 + i * 32 + lane;
            const int sl = sd + (row >> 10);
            uint32_t r[4];
            ldsm4t(r, ring + (sl % NSLOT) * SLOT_BYTES + (row & 1023) * 16);
            mma16816(c0, af[4 * i], 0, af[4 * i + 1], 0, r[0], r[1]);
            mma16816(c1, af[4 * i + 2], 0, af[4 * i + 3], 0, r[2], r[3]);
        }
        if (has_ffn) cbar();
        if (g < 4) *reinterpret_cast<float2*>(red + warp * 128 + g * 8 + 2 * t) = make_float2(c0[0] + c1[0], c0[1] + c1[1]);
        cbar();
        if (tid < 16) {
            float s0 = 0.f, s1 = 0.f;
#pragma unroll
            for (int w = 0; w < 8; w++) {
                float2 v = *reinterpret_cast<float2*>(red + w * 128 + tid * 2);
                s0 += v.x; s1 += v.y;
            }
            const float y0 = bflo(x1w) + bfr(bflo(gb2) * bfr(s0));
            const float y1 = bfhi(x1w) + bfr(bfhi(gb2) * bfr(s1));
            *reinterpret_cast<uint32_t*>(p.out + (tid >> 2) * 512 + 8 * (j - DOWN0) + 2 * (tid & 3)) = pack2(y0, y1);
        }
        PROF(13);
    }
}

typedef CUresult (*EncodeFn)(CUtensorMap*, CUtensorMapDataType, cuuint32_t, void*, const cuuint64_t*, const cuuint64_t*,
                             const cuuint32_t*, const cuuint32_t*, CUtensorMapInterleave, CUtensorMapSwizzle,
                             CUtensorMapL2promotion, CUtensorMapFloatOOBfill);

void make2d(EncodeFn enc, CUtensorMap* m, const void* ptr, uint64_t cols, uint64_t rows, uint32_t bcols, uint32_t brows,
            CUtensorMapSwizzle sw, CUtensorMapL2promotion promo) {
    cuuint64_t gd[2] = {cols, rows};
    cuuint64_t gs[1] = {cols * 2};
    cuuint32_t bx[2] = {bcols, brows};
    cuuint32_t es[2] = {1, 1};
    enc(m, CU_TENSOR_MAP_DATA_TYPE_BFLOAT16, 2, const_cast<void*>(ptr), gd, gs, bx, es, CU_TENSOR_MAP_INTERLEAVE_NONE, sw,
        promo, CU_TENSOR_MAP_FLOAT_OOB_FILL_NONE);
}
void makekv(EncodeFn enc, CUtensorMap* m, const void* ptr) {
    cuuint64_t gd[3] = {64, 262144, 2};
    cuuint64_t gs[2] = {256, 128};
    cuuint32_t bx[3] = {64, 64, 2};
    cuuint32_t es[3] = {1, 1, 1};
    enc(m, CU_TENSOR_MAP_DATA_TYPE_BFLOAT16, 3, const_cast<void*>(ptr), gd, gs, bx, es, CU_TENSOR_MAP_INTERLEAVE_NONE,
        CU_TENSOR_MAP_SWIZZLE_128B, CU_TENSOR_MAP_L2_PROMOTION_L2_256B, CU_TENSOR_MAP_FLOAT_OOB_FILL_NONE);
}

}

extern "C" void kernel_launch(void* const* d_in, const int* in_sizes, int n_in, void* d_out, int out_size) {
    (void)in_sizes; (void)n_in; (void)out_size;
    void* fn = nullptr;
    cudaDriverEntryPointQueryResult st;
    cudaGetDriverEntryPoint("cuTensorMapEncodeTiled", &fn, cudaEnableDefault, &st);
    EncodeFn enc = (EncodeFn)fn;
    Params p;
    makekv(enc, &p.k, d_in[1]);
    makekv(enc, &p.v, d_in[2]);
    make2d(enc, &p.wmodA, d_in[10], 3072, 512, 8, 256, CU_TENSOR_MAP_SWIZZLE_NONE, CU_TENSOR_MAP_L2_PROMOTION_L2_128B);
    make2d(enc, &p.wmodB, d_in[10], 3072, 512, 16, 256, CU_TENSOR_MAP_SWIZZLE_32B, CU_TENSOR_MAP_L2_PROMOTION_L2_128B);
    make2d(enc, &p.wq, d_in[3], 4096, 512, 32, 256, CU_TENSOR_MAP_SWIZZLE_64B, CU_TENSOR_MAP_L2_PROMOTION_L2_128B);
    make2d(enc, &p.wo, d_in[4], 512, 4096, 64, 128, CU_TENSOR_MAP_SWIZZLE_128B, CU_TENSOR_MAP_L2_PROMOTION_L2_128B);
    make2d(enc, &p.wg, d_in[6], 1792, 512, 16, 256, CU_TENSOR_MAP_SWIZZLE_32B, CU_TENSOR_MAP_L2_PROMOTION_L2_128B);
    make2d(enc, &p.wu, d_in[7], 1792, 512, 16, 256, CU_TENSOR_MAP_SWIZZLE_32B, CU_TENSOR_MAP_L2_PROMOTION_L2_128B);
    make2d(enc, &p.wd, d_in[8], 512, 1792, 8, 256, CU_TENSOR_MAP_SWIZZLE_NONE, CU_TENSOR_MAP_L2_PROMOTION_L2_128B);
    p.x = (const bf16*)d_in[0];
    p.c = (const bf16*)d_in[9];
    p.out = (bf16*)d_out;
    cudaFuncSetAttribute(fused_kernel, cudaFuncAttributeMaxDynamicSharedMemorySize, SM_TOTAL);
    fused_kernel<<<NCTA, NTHREADS, SM_TOTAL>>>(p);
}
```

```cpp
#include <cuda_runtime.h>
#include <cuda.h>
#include <cuda_bf16.h>
#include <stdint.h>

namespace {

typedef unsigned long long u64;
typedef __nv_bfloat16 bf16;

constexpr int NCTA = 128;
constexpr int NTHREADS = 320;
constexpr int NSLOT = 13;
constexpr int SLOT_BYTES = 16384;
#define INFLIGHT 3
#define INFLIGHT_LO 2
#define INFLIGHT_HI 4
#define INFLIGHT_TAIL 2
constexpr int GATE_MARGIN = 64;
#define RX 4
#define RA 1
constexpr int ADAPT_TH = 40;
constexpr int RING0 = 3, NRING = NSLOT - RING0;
constexpr int K_FETCH = 16;
constexpr int NMODB = 96;
__device__ __forceinline__ int ring_k(int k) { return 2 * k; }
constexpr int PERM = 2;
__device__ __forceinline__ int tile_row(int t) { return (((t & ((1 << PERM) - 1)) << (7 - PERM)) + ((t & 127) >> PERM)) * 64; }
__device__ __forceinline__ int ring_slot(int r) { return RING0 + r % NRING; }
__device__ __forceinline__ int ring_par(int r) { return (r / NRING) & 1; }
constexpr int NSTATIC = 4;
constexpr int PAIR_TILES = 128;
enum { LD_WMODA, LD_WQ0, LD_WQ1, LD_WO0, LD_WO1, LD_WMODB, LD_WG, LD_WU, LD_WD0, LD_WD1, LD_K, LD_V };
constexpr int NFFN = 112;
constexpr int DOWN0 = 64;

constexpr int SM_RING = 0;
constexpr int SM_H = SM_RING + NSLOT * SLOT_BYTES;
constexpr int SM_SC = SM_H + 4 * 520 * 2;
constexpr int SM_RED = SM_SC + 4096;
constexpr int SM_O = SM_RED + 8 * 128 * 4;
constexpr int SM_ML = SM_O + 4 * 136 * 2;
constexpr int SM_BAR = SM_ML + 8 * 4 * 8;
constexpr int SM_FLAG = SM_BAR + 2 * NSLOT * 8;
constexpr int SM_TICK = SM_FLAG + 16;
constexpr int SM_TOTAL = SM_TICK + 48;
static_assert(INFLIGHT_HI <= 4 && INFLIGHT_TAIL <= 4, "window history");
static_assert(SM_TOTAL <= 232448 - 1024, "smem");
static_assert(SM_H % 16 == 0 && SM_SC % 16 == 0 && SM_RED % 16 == 0 && SM_O % 16 == 0 && SM_ML % 16 == 0 && SM_BAR % 8 == 0, "align");

struct alignas(64) Params {
    CUtensorMap k, v, wmodB, wq, wo, wg, wu, wd, wmodA;
    const bf16* x;
    const bf16* c;
    bf16* out;
};

__device__ unsigned int g_epoch;
__device__ unsigned int g_tile[33 * 32];
__device__ __align__(128) u64 g_h[128 * 8];
__device__ __align__(128) u64 g_ga[4 * 256];
__device__ __align__(128) u64 g_modB[4 * 768];
__device__ __align__(128) u64 g_q[4 * 32 * 64];
__device__ __align__(128) uint4 g_part[32 * 4 * 4 * 64];
__device__ __align__(128) u64 g_p2[32 * 4 * 256 * 2];
__device__ __align__(128) u64 g_x1[RX * 4 * 256];
__device__ __align__(128) u64 g_act[RA * NFFN * 32];

#define PROF(i) do {} while (0)
#define PROF_DECL
#define PROF2(n) do {} while (0)
#define PW(i) do {} while (0)
#define PROF_END do {} while (0)

constexpr int SPIN_LIMIT = 1 << 24;

__device__ __forceinline__ uint32_t smem_u32(const void* p) { return (uint32_t)__cvta_generic_to_shared(p); }
__device__ __forceinline__ void mbar_init(uint32_t bar, uint32_t cnt) {
    asm volatile("mbarrier.init.shared.b64 [%0], %1;" ::"r"(bar), "r"(cnt) : "memory");
}
__device__ __forceinline__ void mbar_expect_tx(uint32_t bar, uint32_t bytes) {
    asm volatile("mbarrier.arrive.expect_tx.shared.b64 _, [%0], %1;" ::"r"(bar), "r"(bytes) : "memory");
}
__device__ __forceinline__ void mbar_arrive(uint32_t bar) {
    asm volatile("mbarrier.arrive.shared.b64 _, [%0];" ::"r"(bar) : "memory");
}
__device__ __forceinline__ bool mbar_try(uint32_t bar, uint32_t parity) {
    uint32_t ok;
    asm volatile("{\n.reg .pred p;\nmbarrier.try_wait.parity.shared.b64 p, [%1], %2;\nselp.u32 %0, 1, 0, p;\n}"
                 : "=r"(ok) : "r"(bar), "r"(parity) : "memory");
    return ok;
}
__device__ __forceinline__ bool mbar_test(uint32_t bar, uint32_t parity) {
    uint32_t ok;
    asm volatile("{\n.reg .pred p;\nmbarrier.test_wait.parity.shared.b64 p, [%1], %2;\nselp.u32 %0, 1, 0, p;\n}"
                 : "=r"(ok) : "r"(bar), "r"(parity) : "memory");
    return ok;
}
__device__ __forceinline__ void mbar_wait(uint32_t bar, uint32_t parity) {
    int n = 0;
    while (!mbar_try(bar, parity)) {
        if (++n > SPIN_LIMIT) __trap();
    }
}
__device__ __forceinline__ void tma_2d(uint32_t dst, const CUtensorMap* m, uint32_t bar, int c0, int c1, u64 pol) {
    asm volatile("cp.async.bulk.tensor.2d.shared::cluster.global.mbarrier::complete_tx::bytes.L2::cache_hint [%0], [%1, {%3, %4}], [%2], %5;"
                 ::"r"(dst), "l"(m), "r"(bar), "r"(c0), "r"(c1), "l"(pol) : "memory");
}
__device__ __forceinline__ void tma_3d(uint32_t dst, const CUtensorMap* m, uint32_t bar, int c0, int c1, int c2, u64 pol) {
    asm volatile("cp.async.bulk.tensor.3d.shared::cluster.global.mbarrier::complete_tx::bytes.L2::cache_hint [%0], [%1, {%3, %4, %5}], [%2], %6;"
                 ::"r"(dst), "l"(m), "r"(bar), "r"(c0), "r"(c1), "r"(c2), "l"(pol) : "memory");
}
__device__ __forceinline__ void ldsm4(uint32_t (&r)[4], uint32_t addr) {
    asm volatile("ldmatrix.sync.aligned.m8n8.x4.shared.b16 {%0,%1,%2,%3}, [%4];"
                 : "=r"(r[0]), "=r"(r[1]), "=r"(r[2]), "=r"(r[3]) : "r"(addr) : "memory");
}
__device__ __forceinline__ void ldsm4t(uint32_t (&r)[4], uint32_t addr) {
    asm volatile("ldmatrix.sync.aligned.m8n8.x4.trans.shared.b16 {%0,%1,%2,%3}, [%4];"
                 : "=r"(r[0]), "=r"(r[1]), "=r"(r[2]), "=r"(r[3]) : "r"(addr) : "memory");
}
__device__ __forceinline__ void mma16816(float (&c)[4], uint32_t a0, uint32_t a1, uint32_t a2, uint32_t a3, uint32_t b0, uint32_t b1) {
    asm volatile("mma.sync.aligned.m16n8k16.row.col.f32.bf16.bf16.f32 {%0,%1,%2,%3}, {%4,%5,%6,%7}, {%8,%9}, {%0,%1,%2,%3};"
                 : "+f"(c[0]), "+f"(c[1]), "+f"(c[2]), "+f"(c[3])
                 : "r"(a0), "r"(a1), "r"(a2), "r"(a3), "r"(b0), "r"(b1));
}
__device__ __forceinline__ uint32_t movmat(uint32_t a) {
    uint32_t d;
    asm volatile("movmatrix.sync.aligned.m8n8.trans.b16 %0, %1;" : "=r"(d) : "r"(a));
    return d;
}
__device__ __forceinline__ void cbar() { asm volatile("bar.sync 1, 256;" ::: "memory"); }

__device__ __forceinline__ float bfr(float x) {
    uint32_t u;
    asm("cvt.rn.bf16x2.f32 %0, %1, %2;" : "=r"(u) : "f"(x), "f"(0.0f));
    return __uint_as_float(u);
}
__device__ __forceinline__ uint32_t pack2(float lo, float hi) {
    __nv_bfloat162 v = __floats2bfloat162_rn(lo, hi);
    return *reinterpret_cast<uint32_t*>(&v);
}
__device__ __forceinline__ float bflo(uint32_t w) { return __uint_as_float(w << 16); }
__device__ __forceinline__ float bfhi(uint32_t w) { return __uint_as_float(w & 0xffff0000u); }
__device__ __forceinline__ float ex2(float x) {
    float y;
    asm("ex2.approx.ftz.f32 %0, %1;" : "=f"(y) : "f"(x));
    return y;
}

__device__ __forceinline__ void ll_st1(u64* p, uint32_t d, uint32_t ep) {
    u64 v = ((u64)ep << 32) | d;
    asm volatile("st.relaxed.gpu.global.u64 [%0], %1;" ::"l"(p), "l"(v) : "memory");
}
__device__ __forceinline__ void ll_st2(u64* p, uint32_t d0, uint32_t d1, uint32_t ep) {
    u64 v0 = ((u64)ep << 32) | d0, v1 = ((u64)ep << 32) | d1;
    asm volatile("st.relaxed.gpu.global.v2.u64 [%0], {%1, %2};" ::"l"(p), "l"(v0), "l"(v1) : "memory");
}
__device__ __forceinline__ bool ll_ld1(const u64* p, uint32_t& d, uint32_t ep) {
    u64 v;
    asm volatile("ld.relaxed.gpu.global.u64 %0, [%1];" : "=l"(v) : "l"(p) : "memory");
    d = (uint32_t)v;
    return (uint32_t)(v >> 32) == ep;
}
__device__ __forceinline__ bool ll_ld2(const u64* p, uint32_t& d0, uint32_t& d1, uint32_t ep) {
    u64 v0, v1;
    asm volatile("ld.relaxed.gpu.global.v2.u64 {%0, %1}, [%2];" : "=l"(v0), "=l"(v1) : "l"(p) : "memory");
    d0 = (uint32_t)v0;
    d1 = (uint32_t)v1;
    return ((uint32_t)(v0 >> 32) == ep) & ((uint32_t)(v1 >> 32) == ep);
}
__device__ __forceinline__ void st128(void* p, uint32_t a, uint32_t b, uint32_t c, uint32_t d) {
    asm volatile("{\n.reg .b128 t;\n.reg .b64 lo, hi;\nmov.b64 lo, {%1,%2};\nmov.b64 hi, {%3,%4};\nmov.b128 t, {lo, hi};\n"
                 "st.relaxed.gpu.global.b128 [%0], t;\n}" ::"l"(p), "r"(a), "r"(b), "r"(c), "r"(d) : "memory");
}
__device__ __forceinline__ bool ld128(const void* p, uint32_t& a, uint32_t& b, uint32_t& c, uint32_t ep) {
    uint32_t d;
    asm volatile("{\n.reg .b128 t;\n.reg .b64 lo, hi;\nld.relaxed.gpu.global.b128 t, [%4];\nmov.b128 {lo, hi}, t;\n"
                 "mov.b64 {%0,%1}, lo;\nmov.b64 {%2,%3}, hi;\n}" : "=r"(a), "=r"(b), "=r"(c), "=r"(d) : "l"(p) : "memory");
    return d == ep;
}
#define POLL(ok_expr)                                           \
    do {                                                        \
        int _n = 0;                                             \
        while (true) {                                          \
            const bool _ok = (ok_expr);                         \
            if (__all_sync(0xffffffffu, _ok)) break;            \
            if (++_n > SPIN_LIMIT) __trap();                    \
        }                                                       \
    } while (0)

__device__ __forceinline__ uint32_t ldg32(const void* p) {
    uint32_t v;
    asm volatile("ld.global.nc.u32 %0, [%1];" : "=r"(v) : "l"(p));
    return v;
}
__device__ __forceinline__ uint4 ldg128(const void* p) {
    uint4 v;
    asm volatile("ld.global.nc.v4.u32 {%0,%1,%2,%3}, [%4];" : "=r"(v.x), "=r"(v.y), "=r"(v.z), "=r"(v.w) : "l"(p));
    return v;
}
__device__ __forceinline__ float silu_f(float x) { return __fdividef(x, 1.0f + __expf(-x)); }
__device__ __forceinline__ float lg2(float x) {
    float y;
    asm("lg2.approx.ftz.f32 %0, %1;" : "=f"(y) : "f"(x));
    return y;
}
__device__ __forceinline__ float sqrt_f(float x) {
    float y;
    asm("sqrt.approx.f32 %0, %1;" : "=f"(y) : "f"(x));
    return y;
}

__device__ __forceinline__ float warp_sum(float v) {
#pragma unroll
    for (int o = 16; o > 0; o >>= 1) v += __shfl_xor_sync(0xffffffffu, v, o);
    return v;
}

__device__ __forceinline__ void issue_load(const Params& p, int kind, int j, uint32_t dst, uint32_t fb, int row, u64 pol, u64 poln) {
    if (kind >= LD_K) {
        mbar_expect_tx(fb, 16384);
        tma_3d(dst, kind == LD_V ? &p.v : &p.k, fb, 0, row, 0, pol);
        return;
    }
    const CUtensorMap* m;
    int c0, c1 = 0, nbox = 2, bytes = 8192;
    if (kind <= LD_WQ1) { m = &p.wq; c0 = 32 * j; c1 = (kind - LD_WQ0) * 256; nbox = 1; bytes = 16384; }
    else if (kind <= LD_WO1) { m = &p.wo; c0 = (j & 3) * 128 + (kind - LD_WO0) * 64; c1 = (j >> 2) * 128; nbox = 1; bytes = 16384; }
    else if (kind == LD_WMODB) { m = &p.wmodB; c0 = 1536 + 16 * j; }
    else if (kind <= LD_WU) { m = kind == LD_WU ? &p.wu : &p.wg; c0 = 16 * j; }
    else { m = &p.wd; c0 = 8 * (j - DOWN0); c1 = (kind - LD_WD0) * 1024; nbox = kind == LD_WD1 ? 3 : 4; bytes = 4096; }
    mbar_expect_tx(fb, nbox * bytes);
#pragma unroll 1
    for (int q = 0; q < nbox; q++) tma_2d(dst + q * bytes, m, fb, c0, c1 + q * 256, poln);
}

__global__ void __launch_bounds__(NTHREADS, 1) fused_kernel(const __grid_constant__ Params p) {
    extern __shared__ __align__(1024) unsigned char smem[];
    const uint32_t sbase = smem_u32(smem);
    const uint32_t ring = sbase + SM_RING;
    const uint32_t bar_full = sbase + SM_BAR, bar_empty = bar_full + NSLOT * 8;
    const int tid = threadIdx.x, warp = tid >> 5, lane = tid & 31;
    const int j = blockIdx.x;
    const int kvh = j & 7, ab = (j >> 3) & 3, split = j >> 5;
    const bool has_ffn = j < NFFN, has_down = j >= DOWN0, has_h = j < 64;

    volatile uint32_t* ep_s = reinterpret_cast<volatile uint32_t*>(smem + SM_FLAG + 12);
    volatile int* tk_req = reinterpret_cast<volatile int*>(smem + SM_TICK);
    volatile u64* tk_val = reinterpret_cast<volatile u64*>(smem + SM_TICK + 16);
    volatile int* t_final = reinterpret_cast<volatile int*>(smem + SM_FLAG + 4);
    PROF_DECL
    if (warp == 9) {
        asm volatile("bar.sync 2, 320;" ::: "memory");
        if (lane != 0) return;
        uint32_t e0;
        int spin = 0;
        while ((e0 = *ep_s) == 0) { if (++spin > SPIN_LIMIT) __trap(); }
        unsigned int* tk = &g_tile[(j & 31) * 32 + ((e0 ^ 1) & 1)];
        unsigned int* gk = &g_tile[32 * 32 + ((e0 ^ 1) & 1)];
#pragma unroll 1
        for (int i = 0;; i++) {
            int rq;
            spin = 0;
            while ((rq = *tk_req) >= 0 && rq <= i) {
                __nanosleep(32);
                if (++spin > SPIN_LIMIT) __trap();
            }
            if (rq < 0) return;
            uint32_t t0, g0;
            asm volatile("atom.relaxed.gpu.global.inc.u32 %0, [%1], 0x7fffffff;" : "=r"(t0) : "l"(tk) : "memory");
            asm volatile("atom.relaxed.gpu.global.inc.u32 %0, [%1], 0x7fffffff;" : "=r"(g0) : "l"(gk) : "memory");
            tk_val[i & 3] = ((u64)(i + 1) << 48) | ((u64)g0 << 24) | t0;
        }
    }
    if (warp == 8) {
        u64 pol = 0, poln = 0;
        const int row0 = (ab * 8 + kvh) * 8192;
        int tile = split;
        if (lane == 0) {
#pragma unroll
            for (int i = 0; i < RING0 + 2; i++) mbar_init(bar_full + i * 8, 1);
            asm volatile("fence.proxy.async.shared::cta;" ::: "memory");
            asm volatile("createpolicy.fractional.L2::evict_first.b64 %0, 1.0;" : "=l"(pol));
            poln = pol;
            mbar_expect_tx(bar_full, has_h ? 16384 : 8192);
            tma_2d(ring, &p.wmodA, bar_full, has_h ? 8 * j : 512 + 8 * j, 0, poln);
            tma_2d(ring + 4096, &p.wmodA, bar_full, has_h ? 8 * j : 512 + 8 * j, 256, poln);
            if (has_h) {
                tma_2d(ring + 8192, &p.wmodA, bar_full, 512 + 8 * j, 0, poln);
                tma_2d(ring + 12288, &p.wmodA, bar_full, 512 + 8 * j, 256, poln);
            }
#pragma unroll
            for (int n = 1; n < RING0 + 2; n++) {
                issue_load(p, n < RING0 ? n : LD_K + (n - RING0), j, ring + n * SLOT_BYTES, bar_full + n * 8, row0 + tile_row(tile), pol, poln);
                PROF2(n);
            }
#pragma unroll
            for (int i = RING0 + 2; i < 2 * NSLOT; i++) mbar_init(bar_full + i * 8, i < NSLOT ? 1 : 4);
            *t_final = 1 << 20;
            *ep_s = 0;
            *tk_req = 1;
            tk_val[0] = 0; tk_val[1] = 0; tk_val[2] = 0; tk_val[3] = 0;
            asm volatile("fence.mbarrier_init.release.cluster;" ::: "memory");
            asm volatile("fence.proxy.async.shared::cta;" ::: "memory");
        }
        if (lane >= 1 && lane < 8) asm volatile("prefetch.tensormap [%0];" ::"l"(&p.k + lane) : "memory");
        __syncwarp();
        asm volatile("bar.arrive 2, 320;" ::: "memory");
        if (lane != 0) return;
        if (sbase & 1023) __trap();
        int rs = 2, ph = 1, kv = 2, nw = 0, nx = 0;
        int ntk = 0, win = INFLIGHT;
        tile += 4;
        bool kv_done = false, gated = false;
        u64 hist = (2u << 24) | (4u << 16) | (6u << 8) | 8u;
        const int nw_total = (has_ffn ? 2 : 0) + (has_down ? 2 : 0), nx_total = j < NMODB ? 3 : 2;
#pragma unroll 1
        for (int n = RING0 + 2; nw < nw_total; n++) {
            int kind = LD_K + (kv & 1), slot = RING0 + rs, par = ph;
            if (!kv_done && !(kv & 1) && tile >= PAIR_TILES) { kv_done = true; *t_final = kv >> 1; *tk_req = -1; }
            const bool area = kv_done && nx < nx_total;
            if (area) {
                kind = LD_WO0 + nx; slot = nx == 2 ? 0 : 1 + nx; par = 0;
            } else if (kv_done) {
                kind = LD_WG + nw + (has_ffn ? 0 : 2);
            }
            if (kv_done && !gated) {
                gated = true;
                const unsigned int* gk = &g_tile[32 * 32 + ((*ep_s ^ 1) & 1)];
                int spin = 0;
                uint32_t gc;
                do {
                    asm volatile("ld.relaxed.gpu.global.u32 %0, [%1];" : "=r"(gc) : "l"(gk) : "memory");
                } while (gc < 32 * (PAIR_TILES - 4 * NSTATIC + 4) - GATE_MARGIN && ++spin < 4096);
            }
            mbar_wait(bar_empty + slot * 8, par);
            {
                const uint32_t e = (uint32_t)(hist >> (8 * ((kv_done ? INFLIGHT_TAIL : win) - 1))) & 0xff;
                mbar_wait(bar_full + (e >> 1) * 8, e & 1);
                hist = (hist << 8) | (u64)(slot * 2 + (par ^ 1));
            }
            issue_load(p, kind, j, ring + slot * SLOT_BYTES, bar_full + slot * 8, row0 + tile_row(tile), pol, poln);
            PROF2(n);
            if (kind == LD_K && kv >= 2 * NSTATIC) *tk_req = ntk + 1;
            if (kind == LD_V) {
                if (kv >= 2 * NSTATIC - 2) {
                    u64 tv;
                    int spin = 0;
                    while ((int)((tv = tk_val[ntk & 3]) >> 48) != ntk + 1) { if (++spin > SPIN_LIMIT) __trap(); }
                    ntk++;
                    tile = (int)(tv & 0xffffff) + 4 * NSTATIC;
                    const int lag = (int)((tv >> 24) & 0xffffff) + (128 * NSTATIC - 16) - tile * 32;
                    win = lag > ADAPT_TH ? INFLIGHT_HI : (lag < -ADAPT_TH ? INFLIGHT_LO : INFLIGHT);
                } else {
                    tile += 4;
                }
            }
            if (kind >= LD_K) kv++;
            if (area) {
                nx++;
            } else {
                if (kv_done) nw++;
                if (++rs == NRING) { rs = 0; ph ^= 1; }
            }
        }
        return;
    }

    const int g = lane >> 2, t = lane & 3;
    unsigned int ep;
    asm volatile("ld.relaxed.gpu.global.u32 %0, [%1];" : "=r"(ep) : "l"(&g_epoch) : "memory");
    uint32_t sc[8];
    {
        const bf16* cw = p.c + (g & 3) * 512 + warp * 64 + 2 * t;
#pragma unroll
        for (int i = 0; i < 8; i++) sc[i] = ldg32(cw + i * 8);
    }
    const bf16* xr = p.x + (tid >> 6) * 512;
    const uint4 u0 = ldg128(xr + lane * 16), u1 = ldg128(xr + lane * 16 + 8);
    const uint32_t xown = ldg32(p.x + ((tid >> 2) & 3) * 512 + 8 * (j & 63) + 2 * (tid & 3));
    const int rb = j >> 5, rcp = (j & 31) * 8 + (tid & 7);
    const uint32_t xw = ldg32(p.x + rb * 512 + 2 * rcp);

    u64* const mb_h = has_h ? &g_h[16 * j + tid] : &g_ga[(tid >> 2) * 256 + 4 * (j - 64) + (tid & 3)];
    u64* const mb_q = &g_q[((((tid >> 4) * 8 + (j >> 4)) * 8 + 2 * (j & 3) + ((tid >> 3) & 1)) * 4 + ((j >> 2) & 3)) * 8 + (tid & 7)];
    u64* const mb_modB = &g_modB[(tid >> 3) * 768 + 8 * j + (tid & 7)];
    uint4* const mb_part = &g_part[(((kvh * 4 + (tid >> 6)) * 4 + ab) * 4 + split) * 64 + (tid & 63)];
    u64* const mb_p2 = &g_p2[(((j >> 2) * 4 + g) * 256 + (j & 3) * 64 + warp * 8 + t) * 2];
    u64* const mb_x1 = &g_x1[(tid >> 3) * 1024 + rb * 256 + rcp];
    u64* const mb_act = &g_act[(tid & 1) * (NFFN * 32) + j * 32 + (tid >> 1)];
    if (tid < 16) ll_st1(mb_h, 0, 0);
    if (tid < 64) ll_st1(mb_q, 0, 0);
    auto init_tail_boxes = [&]() {
        st128(mb_part, 0, 0, 0, 0);
        if (g < 4) { ll_st2(mb_p2, 0, 0, 0); ll_st2(mb_p2 + 8, 0, 0, 0); }
        if (tid < 8 * RX) ll_st1(mb_x1, 0, 0);
        if (has_ffn && tid < 64 && (RA > 1 || !(tid & 1))) {
#pragma unroll
            for (int c = 0; c < (RA + 1) / 2; c++) ll_st1(mb_act + c * 2 * NFFN * 32, 0, 0);
        }
    };

    float* red = reinterpret_cast<float*>(smem + SM_RED);
    bf16* h_s = reinterpret_cast<bf16*>(smem + SM_H);

#pragma unroll
    for (int i = 0; i < 8; i++) sc[i] = g < 4 ? pack2(silu_f(bflo(sc[i])), silu_f(bfhi(sc[i]))) : 0u;
    PROF(14);
    float2* ln_s = reinterpret_cast<float2*>(smem + SM_ML);
    {
        const uint32_t w[8] = {u0.x, u0.y, u0.z, u0.w, u1.x, u1.y, u1.z, u1.w};
        float sum = 0.f;
#pragma unroll
        for (int i = 0; i < 8; i++) sum += bflo(w[i]) + bfhi(w[i]);
        const float mean = warp_sum(sum) * (1.0f / 512.0f);
        float sq = 0.f;
#pragma unroll
        for (int i = 0; i < 8; i++) {
            const float a = bflo(w[i]) - mean, bb = bfhi(w[i]) - mean;
            sq += a * a + bb * bb;
        }
        const float var = warp_sum(sq) * (1.0f / 512.0f);
        if (lane == 0) ln_s[warp] = make_float2(bfr(mean), bfr(sqrt_f(bfr(bfr(var) + 1e-5f))));
    }
    asm volatile("bar.sync 2, 320;" ::: "memory");
    ep += 1;
    if (ep == 0) ep = 2;
    if (tid == 64) *ep_s = ep;
    if (tid == 32 && j < 33)
        asm volatile("red.relaxed.gpu.global.and.b32 [%0], 0;" ::"l"(&g_tile[j * 32 + (ep & 1)]) : "memory");
    PROF(15);
    {
        const uint32_t slot = ring;
        mbar_wait(bar_full, 0);
        __syncwarp();
        PROF(16);
        float c0[4] = {0.f, 0.f, 0.f, 0.f}, c1[4] = {0.f, 0.f, 0.f, 0.f};
#pragma unroll
        for (int i = 0; i < 2; i++) {
            uint32_t r[4];
            ldsm4t(r, slot + (warp * 64 + i * 32 + lane) * 16);
            mma16816(c0, sc[4 * i], 0, sc[4 * i + 1], 0, r[0], r[1]);
            mma16816(c0, sc[4 * i + 2], 0, sc[4 * i + 3], 0, r[2], r[3]);
            ldsm4t(r, slot + (has_h ? 8192 : 0) + (warp * 64 + i * 32 + lane) * 16);
            mma16816(c1, sc[4 * i], 0, sc[4 * i + 1], 0, r[0], r[1]);
            mma16816(c1, sc[4 * i + 2], 0, sc[4 * i + 3], 0, r[2], r[3]);
        }
        if (g < 4) {
            *reinterpret_cast<float4*>(red + warp * 128 + (g * 4 + t) * 4) = make_float4(c0[0], c0[1], c1[0], c1[1]);
            uint4* scs = reinterpret_cast<uint4*>(smem + SM_SC) + (warp * 16 + lane) * 2;
            scs[0] = make_uint4(sc[0], sc[1], sc[2], sc[3]);
            scs[1] = make_uint4(sc[4], sc[5], sc[6], sc[7]);
        }
        cbar();
        if (tid < 16) {
            float s0 = 0.f, s1 = 0.f, a0 = 0.f, a1 = 0.f;
#pragma unroll
            for (int w = 0; w < 8; w++) {
                const float4 v = *reinterpret_cast<float4*>(red + w * 128 + tid * 4);
                s0 += v.x; s1 += v.y; a0 += v.z; a1 += v.w;
            }
            const float2 st = ln_s[(tid >> 2) * 2];
            const float n0 = bfr(__fdividef(bfr(bflo(xown) - st.x), st.y)), n1 = bfr(__fdividef(bfr(bfhi(xown) - st.x), st.y));
            const uint32_t hw = pack2(bfr(n0 * bfr(1.0f + bfr(a0))) + bfr(s0), bfr(n1 * bfr(1.0f + bfr(a1))) + bfr(s1));
            ll_st1(mb_h, has_h ? hw : pack2(s0, s1), ep);
        }
        if (warp >= 4 && lane == 0) mbar_arrive(bar_empty);
        __syncwarp();
    }
    PROF(1);
    {
        uint32_t hw[4];
        const u64* ps = &g_h[2 * tid];
        POLL(ll_ld2(ps, hw[0], hw[1], ep) & ll_ld2(ps + 512, hw[2], hw[3], ep));
        PROF(17);
        bf16* hd = h_s + ((tid >> 1) & 3) * 520 + (tid >> 3) * 8 + (tid & 1) * 4;
        *reinterpret_cast<uint2*>(hd) = make_uint2(hw[0], hw[1]);
        *reinterpret_cast<uint2*>(hd + 256) = make_uint2(hw[2], hw[3]);
        cbar();
    }
    PROF(2);
    {
        const int sq = 1 + (warp >> 2);
        const uint32_t slot = ring + sq * SLOT_BYTES;
        mbar_wait(bar_full + sq * 8, 0);
        __syncwarp();
        PROF(18);
        float c0[4] = {0.f, 0.f, 0.f, 0.f}, c1[4] = {0.f, 0.f, 0.f, 0.f};
#pragma unroll
        for (int ks = 0; ks < 4; ks++) {
            const uint32_t* hp = reinterpret_cast<const uint32_t*>(h_s + (g & 3) * 520 + warp * 64 + ks * 16 + 2 * t);
            const uint32_t b0 = hp[0], b1 = hp[4];
            const int row = (warp & 3) * 64 + ks * 16 + (lane & 7) + (lane >> 4) * 8;
            const int sw = (row >> 1) & 3;
            const int ch = (lane >> 3) & 1;
            uint32_t a[4];
            ldsm4t(a, slot + row * 64 + ((ch ^ sw) << 4));
            mma16816(c0, a[0], a[1], a[2], a[3], b0, b1);
            ldsm4t(a, slot + row * 64 + (((2 + ch) ^ sw) << 4));
            mma16816(c1, a[0], a[1], a[2], a[3], b0, b1);
        }
        if (t < 2) {
            float* rw = red + warp * 128 + 2 * t;
            *reinterpret_cast<float2*>(rw + g * 4) = make_float2(c0[0], c0[1]);
            *reinterpret_cast<float2*>(rw + (g + 8) * 4) = make_float2(c0[2], c0[3]);
            *reinterpret_cast<float2*>(rw + (g + 16) * 4) = make_float2(c1[0], c1[1]);
            *reinterpret_cast<float2*>(rw + (g + 24) * 4) = make_float2(c1[2], c1[3]);
        }
        cbar();
        if (tid < 64) {
            const int b = tid >> 4, ksl = (tid >> 3) & 1, tt = (tid >> 1) & 3, hi = tid & 1;
            const int col = 16 * ksl + 8 * hi + 2 * tt;
            float s0 = 0.f, s1 = 0.f;
#pragma unroll
            for (int w = 0; w < 8; w++) {
                s0 += red[w * 128 + col * 4 + b];
                s1 += red[w * 128 + (col + 1) * 4 + b];
            }
            ll_st1(mb_q, pack2(s0, s1), ep);
        }
        if (warp >= 4 && lane == 0) {
            mbar_arrive(bar_empty + 8);
            mbar_arrive(bar_empty + 16);
        }
        __syncwarp();
    }
    PROF(3);
    const int grp = warp >> 2, wq4 = warp & 3;
    const int krow = wq4 * 16 + (lane & 15);
    const uint32_t koff = krow * 128, kx = krow & 7, kc = lane >> 4;
    const int vrow = wq4 * 16 + (lane & 7) + (lane >> 4) * 8;
    const uint32_t voff = vrow * 128, vx = vrow & 7, vc = (lane >> 3) & 1;
    uint32_t kf[8][4], vf[8][4];
    auto load_k = [&](int sk) {
        const uint32_t kbase = ring + sk * SLOT_BYTES;
#pragma unroll
        for (int ks = 0; ks < 8; ks++) {
            const uint32_t ch = 2 * ks + kc;
            ldsm4(kf[ks], kbase + (ch >> 3) * 8192 + koff + (((ch & 7) ^ kx) << 4));
        }
        __syncwarp();
        if (lane == 0) mbar_arrive(bar_empty + sk * 8);
        __syncwarp();
    };
    auto load_v = [&](int sv, int par) {
        const uint32_t vbase = ring + sv * SLOT_BYTES;
        mbar_wait(bar_full + sv * 8, par);
        __syncwarp();
#pragma unroll
        for (int mt = 0; mt < 8; mt++) {
            const uint32_t ch = 2 * mt + vc;
            ldsm4t(vf[mt], vbase + (ch >> 3) * 8192 + voff + (((ch & 7) ^ vx) << 4));
        }
        __syncwarp();
        if (lane == 0) mbar_arrive(bar_empty + sv * 8);
        __syncwarp();
    };
    uint32_t qf[16];
    uint32_t ga2 = 0;

    float o[8][4];
#pragma unroll
    for (int i = 0; i < 8; i++) { o[i][0] = o[i][1] = o[i][2] = o[i][3] = 0.f; }
    float m0 = -INFINITY, m1 = -INFINITY, l0 = 0.f, l1 = 0.f;
    const float LOG2E = 1.4426950408889634f;
    const float SCALE = 0.08838834764831845f;

    uint32_t kslot_last = 0;
    bool fetched = false;
#pragma unroll 1
    for (int k = grp;; k += 2) {
        const int nk = ring_k(k), nv = nk + 1;
        const int sk = ring_slot(nk), sv = ring_slot(nv);
        const uint32_t kbase = ring + sk * SLOT_BYTES;
        {
            int spin = 0;
            while (k < *t_final && !mbar_test(bar_full + sk * 8, ring_par(nk))) {
                if (++spin > SPIN_LIMIT) __trap();
            }
        }
        __syncwarp();
        const bool last = __any_sync(0xffffffffu, k >= *t_final);
        if (!fetched && (k >= K_FETCH || last)) {
            fetched = true;
            POLL(ll_ld1(&g_ga[rb * 256 + rcp], ga2, ep));
        }
        if (last) break;
        kslot_last = kbase;
        load_k(sk);
        if (k < 2) {
            load_v(sv, 0);
            uint2* q_s = reinterpret_cast<uint2*>(smem + SM_O);
            const u64* qp = &g_q[((ab * 8 + kvh) * 8 + warp) * 32 + (lane & 15) * 2];
            uint32_t q0, q1;
            POLL(ll_ld2(qp, q0, q1, ep));
            if (lane < 16) q_s[warp * 16 + lane] = make_uint2(q0, q1);
            cbar();
#pragma unroll
            for (int ks = 0; ks < 8; ks++) {
                const uint2 v = q_s[ks * 16 + (lane & 15)];
                qf[2 * ks] = v.x; qf[2 * ks + 1] = v.y;
            }
            if (tid < 32 && j < NMODB) ll_st1(mb_modB, 0, 0);
            init_tail_boxes();
            PROF(4);
        }
        float sa[4] = {0.f, 0.f, 0.f, 0.f}, sb_[4] = {0.f, 0.f, 0.f, 0.f};
#pragma unroll
        for (int ks = 0; ks < 8; ks++) {
            if (ks & 1) mma16816(sb_, kf[ks][0], kf[ks][1], kf[ks][2], kf[ks][3], qf[2 * ks], qf[2 * ks + 1]);
            else        mma16816(sa, kf[ks][0], kf[ks][1], kf[ks][2], kf[ks][3], qf[2 * ks], qf[2 * ks + 1]);
        }
        float s[4];
#pragma unroll
        for (int i = 0; i < 4; i++) s[i] = bfr(bfr(sa[i] + sb_[i]) * SCALE);
        float x0 = fmaxf(s[0], s[2]), x1 = fmaxf(s[1], s[3]);
#pragma unroll
        for (int off = 4; off < 32; off <<= 1) {
            x0 = fmaxf(x0, __shfl_xor_sync(0xffffffffu, x0, off));
            x1 = fmaxf(x1, __shfl_xor_sync(0xffffffffu, x1, off));
        }
        const float n0 = fmaxf(m0, x0), n1 = fmaxf(m1, x1);
        const float al0 = ex2((m0 - n0) * LOG2E), al1 = ex2((m1 - n1) * LOG2E);
        m0 = n0; m1 = n1;
        const float p0 = ex2((s[0] - n0) * LOG2E), p1 = ex2((s[1] - n1) * LOG2E);
        const float p2 = ex2((s[2] - n0) * LOG2E), p3 = ex2((s[3] - n1) * LOG2E);
        l0 = l0 * al0 + (p0 + p2);
        l1 = l1 * al1 + (p1 + p3);
        const uint32_t pb0 = movmat(pack2(p0, p1)), pb1 = movmat(pack2(p2, p3));
#pragma unroll
        for (int mt = 0; mt < 8; mt++) {
            o[mt][0] *= al0; o[mt][1] *= al1; o[mt][2] *= al0; o[mt][3] *= al1;
        }
        if (k >= 2) load_v(sv, ring_par(nv));
#pragma unroll
        for (int mt = 0; mt < 8; mt++) mma16816(o[mt], vf[mt][0], vf[mt][1], vf[mt][2], vf[mt][3], pb0, pb1);
    }
    const int T = *t_final;
    const int r_wg = ring_k(T), r_wu = r_wg + 1, r_wd = r_wg + (has_ffn ? 2 : 0);
    PW(0);

    {
#pragma unroll
        for (int off = 4; off < 32; off <<= 1) {
            l0 += __shfl_xor_sync(0xffffffffu, l0, off);
            l1 += __shfl_xor_sync(0xffffffffu, l1, off);
        }
        float* so = reinterpret_cast<float*>(smem + (kslot_last - sbase) + wq4 * 2048);
        float2* ml = reinterpret_cast<float2*>(smem + SM_ML);
        if (t < 2) {
            const int x = t << 4;
#pragma unroll
            for (int mt = 0; mt < 8; mt++) {
                const int d = 16 * mt + g;
                so[(2 * t) * 128 + (d ^ x)] = o[mt][0];
                so[(2 * t + 1) * 128 + (d ^ x)] = o[mt][1];
                so[(2 * t) * 128 + ((d + 8) ^ x)] = o[mt][2];
                so[(2 * t + 1) * 128 + ((d + 8) ^ x)] = o[mt][3];
            }
            if (g == 0) {
                ml[(2 * t) * 8 + warp] = make_float2(m0, l0);
                ml[(2 * t + 1) * 8 + warp] = make_float2(m1, l1);
            }
        }
        const int hd = tid >> 6, dp = tid & 63;
        const float* sw[2];
#pragma unroll
        for (int q = 0; q < 2; q++)
            sw[q] = reinterpret_cast<const float*>(smem + SM_RING + ring_slot(ring_k(((T - 1 - q) & ~1) + q)) * SLOT_BYTES) +
                    hd * 128 + ((2 * dp) ^ ((hd >> 1) << 4));
        cbar();
        PW(1);
        float2 v[8], ov[8];
#pragma unroll
        for (int w = 0; w < 8; w++) {
            v[w] = ml[hd * 8 + w];
            ov[w] = *reinterpret_cast<const float2*>(sw[w >> 2] + (w & 3) * 512);
        }
        const float M = fmaxf(fmaxf(fmaxf(v[0].x, v[1].x), fmaxf(v[2].x, v[3].x)), fmaxf(fmaxf(v[4].x, v[5].x), fmaxf(v[6].x, v[7].x)));
        float Lp[2] = {0.f, 0.f}, p0[2] = {0.f, 0.f}, p1[2] = {0.f, 0.f};
#pragma unroll
        for (int w = 0; w < 8; w++) {
            const float sc_w = ex2((v[w].x - M) * LOG2E);
            Lp[w & 1] += v[w].y * sc_w;
            p0[w & 1] += ov[w].x * sc_w; p1[w & 1] += ov[w].y * sc_w;
        }
        const float L = Lp[0] + Lp[1], a0 = p0[0] + p0[1], a1 = p1[0] + p1[1];
        const float inv = __fdividef(1.0f, L);
        st128(mb_part, __float_as_uint(a0 * inv), __float_as_uint(a1 * inv),
              __float_as_uint(M * LOG2E + lg2(L)), ep);
    }
    PW(2);

    {
        const int head = j >> 2;
        const int b = tid >> 6, dp = tid & 63;
        const int sq = 1 + (warp >> 2);
        const uint32_t slot = ring + sq * SLOT_BYTES;
        mbar_wait(bar_full + sq * 8, 1);
        __syncwarp();
        uint32_t wf[8][4];
        {
            const int ch = 2 * (warp & 3) + (lane >> 4);
#pragma unroll
            for (int ks = 0; ks < 8; ks++) {
                const int row = ks * 16 + (lane & 15);
                ldsm4t(wf[ks], slot + row * 128 + ((ch ^ (row & 7)) << 4));
            }
        }
        uint32_t o0[4], o1[4], ls[4];
        const uint4* pp = &g_part[((head * 4 + b) * 4) * 64 + dp];
        POLL(ld128(pp, o0[0], o1[0], ls[0], ep) & ld128(pp + 64, o0[1], o1[1], ls[1], ep) &
             ld128(pp + 128, o0[2], o1[2], ls[2], ep) & ld128(pp + 192, o0[3], o1[3], ls[3], ep));
        PW(3);
        const float M = fmaxf(fmaxf(__uint_as_float(ls[0]), __uint_as_float(ls[1])), fmaxf(__uint_as_float(ls[2]), __uint_as_float(ls[3])));
        float L = 0.f, a0 = 0.f, a1 = 0.f;
#pragma unroll
        for (int s = 0; s < 4; s++) {
            const float w = ex2(__uint_as_float(ls[s]) - M);
            L += w;
            a0 += __uint_as_float(o0[s]) * w;
            a1 += __uint_as_float(o1[s]) * w;
        }
        const float inv = __fdividef(1.0f, L);
        bf16* o_s = reinterpret_cast<bf16*>(smem + SM_O);
        *reinterpret_cast<uint32_t*>(o_s + b * 136 + 2 * dp) = pack2(a0 * inv, a1 * inv);
        cbar();
        PW(4);
        float c[4][4];
#pragma unroll
        for (int i = 0; i < 4; i++) { c[i][0] = c[i][1] = c[i][2] = c[i][3] = 0.f; }
#pragma unroll
        for (int i = 0; i < 4; i++) {
            uint32_t a[4];
            ldsm4(a, sbase + SM_O + (lane & 3) * 272 + i * 64 + (lane >> 3) * 16);
            mma16816(c[0], a[0], 0, a[1], 0, wf[2 * i][0], wf[2 * i][1]);
            mma16816(c[1], a[0], 0, a[1], 0, wf[2 * i][2], wf[2 * i][3]);
            mma16816(c[2], a[2], 0, a[3], 0, wf[2 * i + 1][0], wf[2 * i + 1][1]);
            mma16816(c[3], a[2], 0, a[3], 0, wf[2 * i + 1][2], wf[2 * i + 1][3]);
        }
        if (g < 4) {
            ll_st2(mb_p2, __float_as_uint(c[0][0] + c[2][0]), __float_as_uint(c[0][1] + c[2][1]), ep);
            ll_st2(mb_p2 + 8, __float_as_uint(c[1][0] + c[3][0]), __float_as_uint(c[1][1] + c[3][1]), ep);
        }
        __syncwarp();
    }
    PW(5);
    if (j < NMODB) {
        const uint4* scs = reinterpret_cast<const uint4*>(smem + SM_SC) + (warp * 16 + (lane & 15)) * 2;
        const uint4 sa_ = scs[0], sb_ = scs[1];
        const uint32_t s8[8] = {sa_.x, sa_.y, sa_.z, sa_.w, sb_.x, sb_.y, sb_.z, sb_.w};
        mbar_wait(bar_full, 1);
        __syncwarp();
        float c0[4] = {0.f, 0.f, 0.f, 0.f}, c1[4] = {0.f, 0.f, 0.f, 0.f};
#pragma unroll
        for (int ks = 0; ks < 4; ks++) {
            const int row = warp * 64 + ks * 16 + (lane & 15);
            const int ch = (lane >> 4) ^ ((row >> 2) & 1);
            uint32_t r[4];
            ldsm4t(r, ring + row * 32 + (ch << 4));
            mma16816(c0, s8[2 * ks], 0, s8[2 * ks + 1], 0, r[0], r[1]);
            mma16816(c1, s8[2 * ks], 0, s8[2 * ks + 1], 0, r[2], r[3]);
        }
        if (g < 4) {
            *reinterpret_cast<float2*>(red + warp * 128 + g * 16 + 2 * t) = make_float2(c0[0], c0[1]);
            *reinterpret_cast<float2*>(red + warp * 128 + g * 16 + 8 + 2 * t) = make_float2(c1[0], c1[1]);
        }
        cbar();
        if (tid < 32) {
            float2 v[8];
#pragma unroll
            for (int w = 0; w < 8; w++) v[w] = *reinterpret_cast<float2*>(red + w * 128 + tid * 2);
            ll_st1(mb_modB, pack2(((v[0].x + v[1].x) + (v[2].x + v[3].x)) + ((v[4].x + v[5].x) + (v[6].x + v[7].x)),
                                  ((v[0].y + v[1].y) + (v[2].y + v[3].y)) + ((v[4].y + v[5].y) + (v[6].y + v[7].y))), ep);
        }
        __syncwarp();
    }
    {
        uint32_t d0, d1;
        const u64* pp = &g_p2[(((tid >> 3) * 4 + rb) * 256 + rcp) * 2];
        POLL(ll_ld2(pp, d0, d1, ep));
        PW(6);
        float s0 = __uint_as_float(d0), s1 = __uint_as_float(d1);
        s0 += __shfl_xor_sync(0xffffffffu, s0, 8);
        s1 += __shfl_xor_sync(0xffffffffu, s1, 8);
        s0 += __shfl_xor_sync(0xffffffffu, s0, 16);
        s1 += __shfl_xor_sync(0xffffffffu, s1, 16);
        float2* xs = reinterpret_cast<float2*>(red + 64);
        if (lane < 8) xs[warp * 64 + lane] = make_float2(s0, s1);
        cbar();
        PW(7);
        if (tid < 8 * RX) {
            float2 v[8];
#pragma unroll
            for (int w = 0; w < 8; w++) v[w] = xs[w * 64 + (tid & 7)];
            s0 = ((v[0].x + v[1].x) + (v[2].x + v[3].x)) + ((v[4].x + v[5].x) + (v[6].x + v[7].x));
            s1 = ((v[0].y + v[1].y) + (v[2].y + v[3].y)) + ((v[4].y + v[5].y) + (v[6].y + v[7].y));
            const float y0 = bflo(xw) + bfr(bflo(ga2) * bfr(s0));
            const float y1 = bfhi(xw) + bfr(bfhi(ga2) * bfr(s1));
            ll_st1(mb_x1, pack2(y0, y1), ep);
        }
        __syncwarp();
    }
    PW(8);
    if (has_ffn) {
        const uint32_t slot_g = ring + ring_slot(r_wg) * SLOT_BYTES, slot_u = ring + ring_slot(r_wu) * SLOT_BYTES;
        uint32_t gf[4][4], uf[4][4];
        {
            const int b = warp & 3, hf = warp >> 2;
            uint2 sbv[2], cbv[2];
            auto load_w = [&]() {
#pragma unroll
                for (int ks = 0; ks < 4; ks++) {
                    const int row = warp * 64 + ks * 16 + (lane & 7) + (lane >> 4) * 8;
                    const int ch = ((lane >> 3) & 1) ^ ((row >> 2) & 1);
                    ldsm4t(gf[ks], slot_g + row * 32 + (ch << 4));
                    ldsm4t(uf[ks], slot_u + row * 32 + (ch << 4));
                }
            };
            const bool pre = __all_sync(0xffffffffu, mbar_test(bar_full + ring_slot(r_wg) * 8, ring_par(r_wg)) && mbar_test(bar_full + ring_slot(r_wu) * 8, ring_par(r_wu)));
            if (pre) load_w();
            const u64* pm = &g_modB[b * 768 + 128 * hf + 2 * lane];
            uint32_t w[8];
            const u64* px = &g_x1[(j % RX) * 1024 + b * 256 + 2 * lane];
            bool mok = ll_ld2(pm, sbv[0].x, sbv[0].y, ep) & ll_ld2(pm + 64, sbv[1].x, sbv[1].y, ep) &
                       ll_ld2(pm + 256, cbv[0].x, cbv[0].y, ep) & ll_ld2(pm + 320, cbv[1].x, cbv[1].y, ep);
            POLL(ll_ld2(px + 128 * hf, w[0], w[1], ep) & ll_ld2(px + 128 * hf + 64, w[2], w[3], ep) &
                 ll_ld2(px + 128 * (hf ^ 1), w[4], w[5], ep) & ll_ld2(px + 128 * (hf ^ 1) + 64, w[6], w[7], ep));
            if (!__all_sync(0xffffffffu, mok))
                POLL(ll_ld2(pm, sbv[0].x, sbv[0].y, ep) & ll_ld2(pm + 64, sbv[1].x, sbv[1].y, ep) &
                     ll_ld2(pm + 256, cbv[0].x, cbv[0].y, ep) & ll_ld2(pm + 320, cbv[1].x, cbv[1].y, ep));
#pragma unroll
            for (int i = 0; i < 2; i++) {
                cbv[i].x = pack2(1.0f + bflo(cbv[i].x), 1.0f + bfhi(cbv[i].x));
                cbv[i].y = pack2(1.0f + bflo(cbv[i].y), 1.0f + bfhi(cbv[i].y));
            }
            PW(9);
            const float x0 = __shfl_sync(0xffffffffu, bflo(w[0]), 0);
            float s1[4], s2[4];
#pragma unroll
            for (int i = 0; i < 4; i++) {
                const float a = bflo(w[2 * i]) - x0, bb = bfhi(w[2 * i]) - x0, cc = bflo(w[2 * i + 1]) - x0, dd = bfhi(w[2 * i + 1]) - x0;
                s1[i] = (a + bb) + (cc + dd);
                s2[i] = (a * a + bb * bb) + (cc * cc + dd * dd);
            }
            float t1 = (s1[0] + s1[1]) + (s1[2] + s1[3]), t2 = (s2[0] + s2[1]) + (s2[2] + s2[3]);
#pragma unroll
            for (int o2 = 16; o2 > 0; o2 >>= 1) {
                t1 += __shfl_xor_sync(0xffffffffu, t1, o2);
                t2 += __shfl_xor_sync(0xffffffffu, t2, o2);
            }
            t1 *= (1.0f / 512.0f);
            const float mean = x0 + t1, m2 = fmaxf(t2 - t1 * t1 * 512.0f, 0.f);
            const float mb = bfr(mean), den = bfr(sqrt_f(bfr(bfr(m2 * (1.0f / 512.0f)) + 1e-5f)));
#pragma unroll
            for (int i = 0; i < 2; i++) {
                const float n0 = bfr(__fdividef(bfr(bflo(w[2 * i]) - mb), den)), n1 = bfr(__fdividef(bfr(bfhi(w[2 * i]) - mb), den));
                const float n2 = bfr(__fdividef(bfr(bflo(w[2 * i + 1]) - mb), den)), n3 = bfr(__fdividef(bfr(bfhi(w[2 * i + 1]) - mb), den));
                uint2 hv;
                hv.x = pack2(bfr(n0 * bflo(cbv[i].x)) + bflo(sbv[i].x), bfr(n1 * bfhi(cbv[i].x)) + bfhi(sbv[i].x));
                hv.y = pack2(bfr(n2 * bflo(cbv[i].y)) + bflo(sbv[i].y), bfr(n3 * bfhi(cbv[i].y)) + bfhi(sbv[i].y));
                *reinterpret_cast<uint2*>(h_s + b * 520 + 256 * hf + 128 * i + 4 * lane) = hv;
            }
            PW(10);
            if (!pre) {
                mbar_wait(bar_full + ring_slot(r_wg) * 8, ring_par(r_wg));
                mbar_wait(bar_full + ring_slot(r_wu) * 8, ring_par(r_wu));
                __syncwarp();
                load_w();
            }
        }
        cbar();
        PW(11);
        float cg[4] = {0.f, 0.f, 0.f, 0.f}, cu[4] = {0.f, 0.f, 0.f, 0.f};
        float cg2[4] = {0.f, 0.f, 0.f, 0.f}, cu2[4] = {0.f, 0.f, 0.f, 0.f};
#pragma unroll
        for (int i = 0; i < 2; i++) {
            uint32_t hb[4];
            ldsm4(hb, sbase + SM_H + (lane & 3) * 1040 + warp * 128 + i * 64 + (lane >> 3) * 16);
            mma16816(cg, gf[2 * i][0], gf[2 * i][1], gf[2 * i][2], gf[2 * i][3], hb[0], hb[1]);
            mma16816(cu, uf[2 * i][0], uf[2 * i][1], uf[2 * i][2], uf[2 * i][3], hb[0], hb[1]);
            mma16816(cg2, gf[2 * i + 1][0], gf[2 * i + 1][1], gf[2 * i + 1][2], gf[2 * i + 1][3], hb[2], hb[3]);
            mma16816(cu2, uf[2 * i + 1][0], uf[2 * i + 1][1], uf[2 * i + 1][2], uf[2 * i + 1][3], hb[2], hb[3]);
        }
        if (t < 2) {
            float* rw = red + warp * 128 + 2 * t;
            *reinterpret_cast<float2*>(rw + g * 4) = make_float2(cg[0] + cg2[0], cg[1] + cg2[1]);
            *reinterpret_cast<float2*>(rw + (g + 8) * 4) = make_float2(cg[2] + cg2[2], cg[3] + cg2[3]);
            *reinterpret_cast<float2*>(rw + 64 + g * 4) = make_float2(cu[0] + cu2[0], cu[1] + cu2[1]);
            *reinterpret_cast<float2*>(rw + 64 + (g + 8) * 4) = make_float2(cu[2] + cu2[2], cu[3] + cu2[3]);
        }
        PW(12);
        cbar();
        PW(13);
        if (warp < 2) {
            const int b = tid >> 4, tt = (tid >> 2) & 3, hi = (tid >> 1) & 1, e = tid & 1;
            const int f = 8 * hi + 2 * tt + e;
            float vg[8], vu[8];
#pragma unroll
            for (int w = 0; w < 8; w++) {
                vg[w] = red[w * 128 + f * 4 + b];
                vu[w] = red[w * 128 + 64 + f * 4 + b];
            }
            const float sgv = ((vg[0] + vg[1]) + (vg[2] + vg[3])) + ((vg[4] + vg[5]) + (vg[6] + vg[7]));
            const float suv = ((vu[0] + vu[1]) + (vu[2] + vu[3])) + ((vu[4] + vu[5]) + (vu[6] + vu[7]));
            const float gv = bfr(sgv), uv = bfr(suv);
            const float inner = 0.7978845608028654f * (gv + 0.044715f * gv * gv * gv);
            const float ge = bfr(__fdividef(gv, 1.0f + __expf(-2.0f * inner)));
            const float av = ge * uv;
            const float other = __shfl_xor_sync(0xffffffffu, av, 1);
            const uint32_t aw = e ? pack2(other, av) : pack2(av, other);
            if (RA > 1 || e == 0) {
#pragma unroll
                for (int c = 0; c < (RA + 1) / 2; c++) ll_st1(mb_act + c * 2 * NFFN * 32, aw, ep);
            }
            __syncwarp();
        }
        if (j == 0 && tid == 64) {
            asm volatile("st.relaxed.gpu.global.u32 [%0], %1;" ::"l"(&g_epoch), "r"(ep) : "memory");
        }
        __syncwarp();
        PW(14);
    }
    if (has_down) {
        const int sd = r_wd;
        mbar_wait(bar_full + ring_slot(sd) * 8, ring_par(sd));
        mbar_wait(bar_full + ring_slot(sd + 1) * 8, ring_par(sd + 1));
        __syncwarp();
        uint32_t r[7][4];
#pragma unroll
        for (int i = 0; i < 7; i++) {
            const int row = warp * 224 + i * 32 + lane;
            const int sl = sd + (row >> 10);
            ldsm4t(r[i], ring + ring_slot(sl) * SLOT_BYTES + (row & 1023) * 16);
        }
        uint32_t x1w, gb2;
        uint32_t af[14];
        const u64* pa = &g_act[(j % RA) * (NFFN * 32) + (warp * 14) * 32 + lane * 2];
        const u64* px = &g_x1[((tid >> 2) & 3) * 256 + 4 * (j - DOWN0) + (tid & 3)];
        const u64* pg = &g_modB[((tid >> 2) & 3) * 768 + 512 + 4 * (j - DOWN0) + (tid & 3)];
        {
            int n = 0;
            while (true) {
                bool ok = ll_ld1(px, x1w, ep) & ll_ld1(pg, gb2, ep);
#pragma unroll
                for (int i = 0; i < 7; i++) ok &= ll_ld2(pa + i * 64, af[2 * i], af[2 * i + 1], ep);
                if (__all_sync(0xffffffffu, ok)) break;
                if (++n > SPIN_LIMIT) __trap();
            }
        }
        PW(15);
        float c[4][4];
#pragma unroll
        for (int i = 0; i < 4; i++) { c[i][0] = c[i][1] = c[i][2] = c[i][3] = 0.f; }
#pragma unroll
        for (int i = 0; i < 7; i++) {
            mma16816(c[(i & 1) * 2], af[2 * i], 0, af[2 * i + 1], 0, r[i][0], r[i][1]);
            mma16816(c[(i & 1) * 2 + 1], af[2 * i], 0, af[2 * i + 1], 0, r[i][2], r[i][3]);
        }
        float v0 = g < 4 ? c[0][0] + c[2][0] : c[1][0] + c[3][0], v1 = g < 4 ? c[0][1] + c[2][1] : c[1][1] + c[3][1];
        v0 += __shfl_xor_sync(0xffffffffu, v0, 16);
        v1 += __shfl_xor_sync(0xffffffffu, v1, 16);
        float* red2 = reinterpret_cast<float*>(smem + SM_O);
        if (g < 4) *reinterpret_cast<float2*>(red2 + warp * 32 + g * 8 + 2 * t) = make_float2(v0, v1);
        cbar();
        PW(16);
        if (tid < 16) {
            float2 v[8];
#pragma unroll
            for (int w = 0; w < 8; w++) v[w] = *reinterpret_cast<float2*>(red2 + w * 32 + tid * 2);
            const float s0 = ((v[0].x + v[1].x) + (v[2].x + v[3].x)) + ((v[4].x + v[5].x) + (v[6].x + v[7].x));
            const float s1 = ((v[0].y + v[1].y) + (v[2].y + v[3].y)) + ((v[4].y + v[5].y) + (v[6].y + v[7].y));
            const float y0 = bflo(x1w) + bfr(bflo(gb2) * bfr(s0));
            const float y1 = bfhi(x1w) + bfr(bfhi(gb2) * bfr(s1));
            *reinterpret_cast<uint32_t*>(p.out + (tid >> 2) * 512 + 8 * (j - DOWN0) + 2 * (tid & 3)) = pack2(y0, y1);
        }
        PW(17);
    }
    PROF_END;
}

#define WPROMO CU_TENSOR_MAP_L2_PROMOTION_L2_128B
#define PPROMO CU_TENSOR_MAP_L2_PROMOTION_L2_128B
#define KPROMO CU_TENSOR_MAP_L2_PROMOTION_L2_128B
typedef CUresult (*EncodeFn)(CUtensorMap*, CUtensorMapDataType, cuuint32_t, void*, const cuuint64_t*, const cuuint64_t*,
                             const cuuint32_t*, const cuuint32_t*, CUtensorMapInterleave, CUtensorMapSwizzle,
                             CUtensorMapL2promotion, CUtensorMapFloatOOBfill);

void make2d(EncodeFn enc, CUtensorMap* m, const void* ptr, uint64_t cols, uint64_t rows, uint32_t bcols, uint32_t brows,
            CUtensorMapSwizzle sw, CUtensorMapL2promotion promo) {
    cuuint64_t gd[2] = {cols, rows};
    cuuint64_t gs[1] = {cols * 2};
    cuuint32_t bx[2] = {bcols, brows};
    cuuint32_t es[2] = {1, 1};
    enc(m, CU_TENSOR_MAP_DATA_TYPE_BFLOAT16, 2, const_cast<void*>(ptr), gd, gs, bx, es, CU_TENSOR_MAP_INTERLEAVE_NONE, sw,
        promo, CU_TENSOR_MAP_FLOAT_OOB_FILL_NONE);
}
void makekv(EncodeFn enc, CUtensorMap* m, const void* ptr) {
    cuuint64_t gd[3] = {64, 262144, 2};
    cuuint64_t gs[2] = {256, 128};
    cuuint32_t bx[3] = {64, 64, 2};
    cuuint32_t es[3] = {1, 1, 1};
    enc(m, CU_TENSOR_MAP_DATA_TYPE_BFLOAT16, 3, const_cast<void*>(ptr), gd, gs, bx, es, CU_TENSOR_MAP_INTERLEAVE_NONE,
        CU_TENSOR_MAP_SWIZZLE_128B, KPROMO, CU_TENSOR_MAP_FLOAT_OOB_FILL_NONE);
}

}

extern "C" void kernel_launch(void* const* d_in, const int* in_sizes, int n_in, void* d_out, int out_size) {
    (void)in_sizes; (void)n_in; (void)out_size;
    void* fn = nullptr;
    cudaDriverEntryPointQueryResult st;
    cudaGetDriverEntryPoint("cuTensorMapEncodeTiled", &fn, cudaEnableDefault, &st);
    EncodeFn enc = (EncodeFn)fn;
    Params p;
    makekv(enc, &p.k, d_in[1]);
    makekv(enc, &p.v, d_in[2]);
    make2d(enc, &p.wmodB, d_in[10], 3072, 512, 16, 256, CU_TENSOR_MAP_SWIZZLE_32B, WPROMO);
    make2d(enc, &p.wq, d_in[3], 4096, 512, 32, 256, CU_TENSOR_MAP_SWIZZLE_64B, PPROMO);
    make2d(enc, &p.wo, d_in[4], 512, 4096, 64, 128, CU_TENSOR_MAP_SWIZZLE_128B, WPROMO);
    make2d(enc, &p.wg, d_in[6], 1792, 512, 16, 256, CU_TENSOR_MAP_SWIZZLE_32B, WPROMO);
    make2d(enc, &p.wu, d_in[7], 1792, 512, 16, 256, CU_TENSOR_MAP_SWIZZLE_32B, WPROMO);
    make2d(enc, &p.wd, d_in[8], 512, 1792, 8, 256, CU_TENSOR_MAP_SWIZZLE_NONE, WPROMO);
    make2d(enc, &p.wmodA, d_in[10], 3072, 512, 8, 256, CU_TENSOR_MAP_SWIZZLE_NONE, PPROMO);
    p.x = (const bf16*)d_in[0];
    p.c = (const bf16*)d_in[9];
    p.out = (bf16*)d_out;
    cudaFuncSetAttribute(fused_kernel, cudaFuncAttributeMaxDynamicSharedMemorySize, SM_TOTAL);
    fused_kernel<<<NCTA, NTHREADS, SM_TOTAL>>>(p);
}
```
